```python
import torch

def _softmax(x, axis=-1):
    return torch.softmax(x, dim=axis)

def _gelu(x):
    return torch.nn.functional.gelu(x, approximate='tanh')

def _silu(x):
    return torch.nn.functional.silu(x)

def _sigmoid(x):
    return torch.sigmoid(x)

def _layernorm(x, axis=-1, eps=1e-05):
    m = x.mean(dim=axis, keepdim=True)
    v = x.var(dim=axis, keepdim=True, unbiased=False)
    return (x - m) / torch.sqrt(v + eps)

def _scatter_add(tgt, idx, src, axis=0):
    return tgt.clone().index_add_(axis, idx, src)

def _segment_sum(src, seg, n):
    out = torch.zeros((n,) + src.shape[1:], dtype=src.dtype)
    return out.index_add_(0, seg, src)

def _pad(x, pw):
    flat = tuple((v for pair in reversed(pw) for v in pair))
    return torch.nn.functional.pad(x, flat)
kernel_name = 'standalone__video_video_swin__vision'

def setup_inputs():

    _w = lambda a: (lambda t: t.to(torch.bfloat16) if t.is_floating_point() else t)(torch.as_tensor(a))
    T = 4
    H = W = 224 // 7 * 7
    C, win = (192, 7)
    return {'x': _w((lambda *s: torch.randn(*s, dtype=torch.bfloat16) * 0.1)(1, T, H, W, C)), 'wqkv_t': _w((lambda *s: torch.randn(*s, dtype=torch.bfloat16) * 0.1)(C, 3 * C)), 'wo_t': _w((lambda *s: torch.randn(*s, dtype=torch.bfloat16) * 0.1)(C, C)), 'wqkv_s': _w((lambda *s: torch.randn(*s, dtype=torch.bfloat16) * 0.1)(C, 3 * C)), 'wo_s': _w((lambda *s: torch.randn(*s, dtype=torch.bfloat16) * 0.05)(C, C))}

def reference(x, wqkv_t, wo_t, wqkv_s, wo_s):
    B, T, H, W, C = x.shape
    win = 7
    scale = C ** (-0.5)
    h = _layernorm(x, axis=-1)
    ht = (lambda x, *d: x.permute(*d))(h, 0, 2, 3, 1, 4).reshape(B * H * W, T, C)
    qkv = ht @ wqkv_t
    q, k, v = (qkv[..., :C].clone(), qkv[..., C:2 * C].clone(), qkv[..., 2 * C:].clone())
    p = _softmax(torch.einsum('btc,bsc->bts', q, k) * scale, axis=-1)
    ot = torch.einsum('bts,bsc->btc', p, v) @ wo_t
    ot = (lambda x, *d: x.permute(*d))(ot.reshape(B, H, W, T, C), 0, 3, 1, 2, 4)
    x = x + ot
    h = _layernorm(x, axis=-1)
    nh, nw = (H // win, W // win)
    hs = h.reshape(B * T, nh, win, nw, win, C)
    hw = (lambda x, *d: x.permute(*d))(hs, 0, 1, 3, 2, 4, 5).reshape(B * T * nh * nw, win * win, C)
    qkv = hw @ wqkv_s
    q, k, v = (qkv[..., :C].clone(), qkv[..., C:2 * C].clone(), qkv[..., 2 * C:].clone())
    p = _softmax(torch.einsum('bqc,bkc->bqk', q, k) * scale, axis=-1)
    os = torch.einsum('bqk,bkc->bqc', p, v) @ wo_s
    os = (lambda x, *d: x.permute(*d))(os.reshape(B * T, nh, nw, win, win, C), 0, 1, 3, 2, 4, 5)
    os = os.reshape(B, T, H, W, C)
    return x + os
```

```cpp
#include <cuda_runtime.h>
#include <cuda_bf16.h>
#include <cuda.h>
#include <stdint.h>

#define C_DIM 192
#define T_DIM 4
#define HW_DIM 50176
#define NT1 3136
#define NT2 4096

#define SLOT_BYTES 24576
#define BLK_BYTES 8192
#define WMAT_BYTES 73728
#define WBLK_BYTES 24576
#define NSLOT 3

#define SM_WM 0
#define SM_WU WMAT_BYTES
#define SM_SLOT (2 * WMAT_BYTES)
#define SM_STATS (SM_SLOT + NSLOT * SLOT_BYTES)
#define SM_MSUM (SM_STATS + NSLOT * 1024)
#define SM_BAR (SM_MSUM + 768)
#define SM_TOTAL (SM_BAR + 256)

__device__ __align__(1024) unsigned char g_wimg[2][2][WMAT_BYTES];
#define TL(idx)
#define TLP(idx)

__device__ __forceinline__ uint32_t smem_u32(const void* p) { return (uint32_t)__cvta_generic_to_shared(p); }

__device__ __forceinline__ void mbar_init(uint32_t bar, uint32_t count) {
  asm volatile("mbarrier.init.shared::cta.b64 [%0], %1;" ::"r"(bar), "r"(count) : "memory");
}
__device__ __forceinline__ void mbar_expect_tx(uint32_t bar, uint32_t bytes) {
  asm volatile("mbarrier.arrive.expect_tx.shared::cta.b64 _, [%0], %1;" ::"r"(bar), "r"(bytes) : "memory");
}
__device__ __forceinline__ void mbar_arrive(uint32_t bar) {
  asm volatile("mbarrier.arrive.shared::cta.b64 _, [%0];" ::"r"(bar) : "memory");
}
__device__ __forceinline__ bool mbar_try_wait(uint32_t bar, uint32_t parity) {
  uint32_t ok;
  asm volatile(
      "{\n.reg .pred p;\nmbarrier.try_wait.parity.shared::cta.b64 p, [%1], %2;\nselp.u32 %0, 1, 0, p;\n}\n"
      : "=r"(ok)
      : "r"(bar), "r"(parity)
      : "memory");
  return ok != 0;
}
__device__ __forceinline__ void mbar_wait(uint32_t bar, uint32_t parity) {
  for (uint32_t it = 0; it < (1u << 24); ++it)
    if (mbar_try_wait(bar, parity)) break;
}
__device__ __forceinline__ void fence_proxy_async() { asm volatile("fence.proxy.async.shared::cta;" ::: "memory"); }
__device__ __forceinline__ void named_bar_sync(int id, int nthreads) {
  asm volatile("bar.sync %0, %1;" ::"r"(id), "r"(nthreads) : "memory");
}

__device__ __forceinline__ void tma_load_3d(uint32_t dst, const CUtensorMap* map, int c0, int c1, int c2, uint32_t bar) {
  asm volatile(
      "cp.async.bulk.tensor.3d.shared::cluster.global.mbarrier::complete_tx::bytes [%0], [%1, {%3, %4, %5}], [%2];"
      ::"r"(dst), "l"(map), "r"(bar), "r"(c0), "r"(c1), "r"(c2) : "memory");
}
__device__ __forceinline__ void tma_load_4d(uint32_t dst, const CUtensorMap* map, int c0, int c1, int c2, int c3, uint32_t bar) {
  asm volatile(
      "cp.async.bulk.tensor.4d.shared::cluster.global.mbarrier::complete_tx::bytes [%0], [%1, {%3, %4, %5, %6}], [%2];"
      ::"r"(dst), "l"(map), "r"(bar), "r"(c0), "r"(c1), "r"(c2), "r"(c3) : "memory");
}
__device__ __forceinline__ void tma_store_3d(const CUtensorMap* map, uint32_t src, int c0, int c1, int c2) {
  asm volatile("cp.async.bulk.tensor.3d.global.shared::cta.bulk_group [%0, {%2, %3, %4}], [%1];"
               ::"l"(map), "r"(src), "r"(c0), "r"(c1), "r"(c2) : "memory");
}
__device__ __forceinline__ void tma_store_4d(const CUtensorMap* map, uint32_t src, int c0, int c1, int c2, int c3) {
  asm volatile("cp.async.bulk.tensor.4d.global.shared::cta.bulk_group [%0, {%2, %3, %4, %5}], [%1];"
               ::"l"(map), "r"(src), "r"(c0), "r"(c1), "r"(c2), "r"(c3) : "memory");
}
__device__ __forceinline__ void tma_prefetch_3d(const CUtensorMap* map, int c0, int c1, int c2) {
  asm volatile("cp.async.bulk.prefetch.tensor.3d.L2.global.tile [%0, {%1, %2, %3}];" ::"l"(map), "r"(c0), "r"(c1), "r"(c2) : "memory");
}
__device__ __forceinline__ void tma_prefetch_4d(const CUtensorMap* map, int c0, int c1, int c2, int c3) {
  asm volatile("cp.async.bulk.prefetch.tensor.4d.L2.global.tile [%0, {%1, %2, %3, %4}];" ::"l"(map), "r"(c0), "r"(c1), "r"(c2), "r"(c3) : "memory");
}
__device__ __forceinline__ void bulk_commit() { asm volatile("cp.async.bulk.commit_group;" ::: "memory"); }
__device__ __forceinline__ void bulk_wait_read0() { asm volatile("cp.async.bulk.wait_group.read 0;" ::: "memory"); }
__device__ __forceinline__ void bulk_wait0() { asm volatile("cp.async.bulk.wait_group 0;" ::: "memory"); }
__device__ __forceinline__ void bulk_load(uint32_t dst, const void* src, uint32_t bytes, uint32_t bar) {
  asm volatile("cp.async.bulk.shared::cluster.global.mbarrier::complete_tx::bytes [%0], [%1], %2, [%3];"
               ::"r"(dst), "l"(src), "r"(bytes), "r"(bar) : "memory");
}

__device__ __forceinline__ void wg_fence() { asm volatile("wgmma.fence.sync.aligned;" ::: "memory"); }
__device__ __forceinline__ void wg_commit() { asm volatile("wgmma.commit_group.sync.aligned;" ::: "memory"); }
__device__ __forceinline__ void wg_wait0() { asm volatile("wgmma.wait_group.sync.aligned 0;" ::: "memory"); }
template <int N>
__device__ __forceinline__ void fence_regs(float (&d)[N]) {
#pragma unroll
  for (int i = 0; i < N; i++) asm volatile("" : "+f"(d[i])::"memory");
}

__device__ __forceinline__ uint64_t make_desc(uint32_t addr, uint32_t lbo, uint32_t sbo) {
  return (uint64_t)((addr & 0x3FFFF) >> 4) | ((uint64_t)(lbo >> 4) << 16) | ((uint64_t)(sbo >> 4) << 32) | (1ull << 62);
}

__device__ __forceinline__ uint32_t pack_bf16(float lo, float hi) {
  uint32_t r;
  asm("cvt.rn.bf16x2.f32 %0, %1, %2;" : "=r"(r) : "f"(hi), "f"(lo));
  return r;
}
__device__ __forceinline__ float bf_lo(uint32_t v) { return __uint_as_float(v << 16); }
__device__ __forceinline__ float bf_hi(uint32_t v) { return __uint_as_float(v & 0xffff0000u); }

__device__ __forceinline__ void ldsm_x4(uint32_t addr, uint32_t& r0, uint32_t& r1, uint32_t& r2, uint32_t& r3) {
  asm volatile("ldmatrix.sync.aligned.m8n8.x4.shared.b16 {%0, %1, %2, %3}, [%4];"
               : "=r"(r0), "=r"(r1), "=r"(r2), "=r"(r3) : "r"(addr) : "memory");
}
__device__ __forceinline__ void stsm_x4(uint32_t addr, uint32_t r0, uint32_t r1, uint32_t r2, uint32_t r3) {
  asm volatile("stmatrix.sync.aligned.m8n8.x4.shared.b16 [%0], {%1, %2, %3, %4};"
               ::"r"(addr), "r"(r0), "r"(r1), "r"(r2), "r"(r3) : "memory");
}
__device__ __forceinline__ float4 lds_f4(uint32_t addr) {
  float4 v;
  asm volatile("ld.shared.v4.f32 {%0, %1, %2, %3}, [%4];" : "=f"(v.x), "=f"(v.y), "=f"(v.z), "=f"(v.w) : "r"(addr));
  return v;
}
__device__ __forceinline__ float2 lds_f2(uint32_t addr) {
  float2 v;
  asm volatile("ld.shared.v2.f32 {%0, %1}, [%2];" : "=f"(v.x), "=f"(v.y) : "r"(addr));
  return v;
}
__device__ __forceinline__ uint4 lds_u4(uint32_t addr) {
  uint4 v;
  asm volatile("ld.shared.v4.u32 {%0, %1, %2, %3}, [%4];" : "=r"(v.x), "=r"(v.y), "=r"(v.z), "=r"(v.w) : "r"(addr));
  return v;
}
__device__ __forceinline__ void sts_f4(uint32_t addr, float4 v) {
  asm volatile("st.shared.v4.f32 [%0], {%1, %2, %3, %4};" ::"r"(addr), "f"(v.x), "f"(v.y), "f"(v.z), "f"(v.w) : "memory");
}
__device__ __forceinline__ void sts_u4(uint32_t addr, uint4 v) {
  asm volatile("st.shared.v4.u32 [%0], {%1, %2, %3, %4};" ::"r"(addr), "r"(v.x), "r"(v.y), "r"(v.z), "r"(v.w) : "memory");
}
__device__ __forceinline__ void sts_f32(uint32_t addr, float v) {
  asm volatile("st.shared.f32 [%0], %1;" ::"r"(addr), "f"(v) : "memory");
}
__device__ __forceinline__ float ex2(float x) {
  float y;
  asm("ex2.approx.ftz.f32 %0, %1;" : "=f"(y) : "f"(x));
  return y;
}

__device__ __forceinline__ void wgmma_m64n192k16_ss(float (&d)[96], uint64_t descA, uint64_t descB, int scaleD) {
  asm volatile("{\n.reg .pred p;\nsetp.ne.b32 p, %98, 0;\n"
    "wgmma.mma_async.sync.aligned.m64n192k16.f32.bf16.bf16 "
    "{%0, %1, %2, %3, %4, %5, %6, %7, %8, %9, %10, %11, %12, %13, %14, %15, %16, %17, %18, %19, %20, %21, %22, %23, %24, %25, %26, %27, %28, %29, %30, %31, %32, %33, %34, %35, %36, %37, %38, %39, %40, %41, %42, %43, %44, %45, %46, %47, %48, %49, %50, %51, %52, %53, %54, %55, %56, %57, %58, %59, %60, %61, %62, %63, %64, %65, %66, %67, %68, %69, %70, %71, %72, %73, %74, %75, %76, %77, %78, %79, %80, %81, %82, %83, %84, %85, %86, %87, %88, %89, %90, %91, %92, %93, %94, %95}, %96, %97, p, 1, 1, 0, 0;\n}\n"
    : "+f"(d[0]), "+f"(d[1]), "+f"(d[2]), "+f"(d[3]), "+f"(d[4]), "+f"(d[5]), "+f"(d[6]), "+f"(d[7]), "+f"(d[8]), "+f"(d[9]), "+f"(d[10]), "+f"(d[11]), "+f"(d[12]), "+f"(d[13]), "+f"(d[14]), "+f"(d[15]), "+f"(d[16]), "+f"(d[17]), "+f"(d[18]), "+f"(d[19]), "+f"(d[20]), "+f"(d[21]), "+f"(d[22]), "+f"(d[23]), "+f"(d[24]), "+f"(d[25]), "+f"(d[26]), "+f"(d[27]), "+f"(d[28]), "+f"(d[29]), "+f"(d[30]), "+f"(d[31]), "+f"(d[32]), "+f"(d[33]), "+f"(d[34]), "+f"(d[35]), "+f"(d[36]), "+f"(d[37]), "+f"(d[38]), "+f"(d[39]), "+f"(d[40]), "+f"(d[41]), "+f"(d[42]), "+f"(d[43]), "+f"(d[44]), "+f"(d[45]), "+f"(d[46]), "+f"(d[47]), "+f"(d[48]), "+f"(d[49]), "+f"(d[50]), "+f"(d[51]), "+f"(d[52]), "+f"(d[53]), "+f"(d[54]), "+f"(d[55]), "+f"(d[56]), "+f"(d[57]), "+f"(d[58]), "+f"(d[59]), "+f"(d[60]), "+f"(d[61]), "+f"(d[62]), "+f"(d[63]), "+f"(d[64]), "+f"(d[65]), "+f"(d[66]), "+f"(d[67]), "+f"(d[68]), "+f"(d[69]), "+f"(d[70]), "+f"(d[71]), "+f"(d[72]), "+f"(d[73]), "+f"(d[74]), "+f"(d[75]), "+f"(d[76]), "+f"(d[77]), "+f"(d[78]), "+f"(d[79]), "+f"(d[80]), "+f"(d[81]), "+f"(d[82]), "+f"(d[83]), "+f"(d[84]), "+f"(d[85]), "+f"(d[86]), "+f"(d[87]), "+f"(d[88]), "+f"(d[89]), "+f"(d[90]), "+f"(d[91]), "+f"(d[92]), "+f"(d[93]), "+f"(d[94]), "+f"(d[95])
    : "l"(descA), "l"(descB), "r"(scaleD));
}

__device__ __forceinline__ void wgmma_m64n192k16_rs(float (&d)[96], uint32_t a0, uint32_t a1, uint32_t a2, uint32_t a3, uint64_t descB, int scaleD) {
  asm volatile("{\n.reg .pred p;\nsetp.ne.b32 p, %101, 0;\n"
    "wgmma.mma_async.sync.aligned.m64n192k16.f32.bf16.bf16 "
    "{%0, %1, %2, %3, %4, %5, %6, %7, %8, %9, %10, %11, %12, %13, %14, %15, %16, %17, %18, %19, %20, %21, %22, %23, %24, %25, %26, %27, %28, %29, %30, %31, %32, %33, %34, %35, %36, %37, %38, %39, %40, %41, %42, %43, %44, %45, %46, %47, %48, %49, %50, %51, %52, %53, %54, %55, %56, %57, %58, %59, %60, %61, %62, %63, %64, %65, %66, %67, %68, %69, %70, %71, %72, %73, %74, %75, %76, %77, %78, %79, %80, %81, %82, %83, %84, %85, %86, %87, %88, %89, %90, %91, %92, %93, %94, %95}, {%96, %97, %98, %99}, %100, p, 1, 1, 0;\n}\n"
    : "+f"(d[0]), "+f"(d[1]), "+f"(d[2]), "+f"(d[3]), "+f"(d[4]), "+f"(d[5]), "+f"(d[6]), "+f"(d[7]), "+f"(d[8]), "+f"(d[9]), "+f"(d[10]), "+f"(d[11]), "+f"(d[12]), "+f"(d[13]), "+f"(d[14]), "+f"(d[15]), "+f"(d[16]), "+f"(d[17]), "+f"(d[18]), "+f"(d[19]), "+f"(d[20]), "+f"(d[21]), "+f"(d[22]), "+f"(d[23]), "+f"(d[24]), "+f"(d[25]), "+f"(d[26]), "+f"(d[27]), "+f"(d[28]), "+f"(d[29]), "+f"(d[30]), "+f"(d[31]), "+f"(d[32]), "+f"(d[33]), "+f"(d[34]), "+f"(d[35]), "+f"(d[36]), "+f"(d[37]), "+f"(d[38]), "+f"(d[39]), "+f"(d[40]), "+f"(d[41]), "+f"(d[42]), "+f"(d[43]), "+f"(d[44]), "+f"(d[45]), "+f"(d[46]), "+f"(d[47]), "+f"(d[48]), "+f"(d[49]), "+f"(d[50]), "+f"(d[51]), "+f"(d[52]), "+f"(d[53]), "+f"(d[54]), "+f"(d[55]), "+f"(d[56]), "+f"(d[57]), "+f"(d[58]), "+f"(d[59]), "+f"(d[60]), "+f"(d[61]), "+f"(d[62]), "+f"(d[63]), "+f"(d[64]), "+f"(d[65]), "+f"(d[66]), "+f"(d[67]), "+f"(d[68]), "+f"(d[69]), "+f"(d[70]), "+f"(d[71]), "+f"(d[72]), "+f"(d[73]), "+f"(d[74]), "+f"(d[75]), "+f"(d[76]), "+f"(d[77]), "+f"(d[78]), "+f"(d[79]), "+f"(d[80]), "+f"(d[81]), "+f"(d[82]), "+f"(d[83]), "+f"(d[84]), "+f"(d[85]), "+f"(d[86]), "+f"(d[87]), "+f"(d[88]), "+f"(d[89]), "+f"(d[90]), "+f"(d[91]), "+f"(d[92]), "+f"(d[93]), "+f"(d[94]), "+f"(d[95])
    : "r"(a0), "r"(a1), "r"(a2), "r"(a3), "l"(descB), "r"(scaleD));
}

__device__ __forceinline__ void wgmma_m64n192k16_rs_tb(float (&d)[96], uint32_t a0, uint32_t a1, uint32_t a2, uint32_t a3, uint64_t descB, int scaleD) {
  asm volatile("{\n.reg .pred p;\nsetp.ne.b32 p, %101, 0;\n"
    "wgmma.mma_async.sync.aligned.m64n192k16.f32.bf16.bf16 "
    "{%0, %1, %2, %3, %4, %5, %6, %7, %8, %9, %10, %11, %12, %13, %14, %15, %16, %17, %18, %19, %20, %21, %22, %23, %24, %25, %26, %27, %28, %29, %30, %31, %32, %33, %34, %35, %36, %37, %38, %39, %40, %41, %42, %43, %44, %45, %46, %47, %48, %49, %50, %51, %52, %53, %54, %55, %56, %57, %58, %59, %60, %61, %62, %63, %64, %65, %66, %67, %68, %69, %70, %71, %72, %73, %74, %75, %76, %77, %78, %79, %80, %81, %82, %83, %84, %85, %86, %87, %88, %89, %90, %91, %92, %93, %94, %95}, {%96, %97, %98, %99}, %100, p, 1, 1, 1;\n}\n"
    : "+f"(d[0]), "+f"(d[1]), "+f"(d[2]), "+f"(d[3]), "+f"(d[4]), "+f"(d[5]), "+f"(d[6]), "+f"(d[7]), "+f"(d[8]), "+f"(d[9]), "+f"(d[10]), "+f"(d[11]), "+f"(d[12]), "+f"(d[13]), "+f"(d[14]), "+f"(d[15]), "+f"(d[16]), "+f"(d[17]), "+f"(d[18]), "+f"(d[19]), "+f"(d[20]), "+f"(d[21]), "+f"(d[22]), "+f"(d[23]), "+f"(d[24]), "+f"(d[25]), "+f"(d[26]), "+f"(d[27]), "+f"(d[28]), "+f"(d[29]), "+f"(d[30]), "+f"(d[31]), "+f"(d[32]), "+f"(d[33]), "+f"(d[34]), "+f"(d[35]), "+f"(d[36]), "+f"(d[37]), "+f"(d[38]), "+f"(d[39]), "+f"(d[40]), "+f"(d[41]), "+f"(d[42]), "+f"(d[43]), "+f"(d[44]), "+f"(d[45]), "+f"(d[46]), "+f"(d[47]), "+f"(d[48]), "+f"(d[49]), "+f"(d[50]), "+f"(d[51]), "+f"(d[52]), "+f"(d[53]), "+f"(d[54]), "+f"(d[55]), "+f"(d[56]), "+f"(d[57]), "+f"(d[58]), "+f"(d[59]), "+f"(d[60]), "+f"(d[61]), "+f"(d[62]), "+f"(d[63]), "+f"(d[64]), "+f"(d[65]), "+f"(d[66]), "+f"(d[67]), "+f"(d[68]), "+f"(d[69]), "+f"(d[70]), "+f"(d[71]), "+f"(d[72]), "+f"(d[73]), "+f"(d[74]), "+f"(d[75]), "+f"(d[76]), "+f"(d[77]), "+f"(d[78]), "+f"(d[79]), "+f"(d[80]), "+f"(d[81]), "+f"(d[82]), "+f"(d[83]), "+f"(d[84]), "+f"(d[85]), "+f"(d[86]), "+f"(d[87]), "+f"(d[88]), "+f"(d[89]), "+f"(d[90]), "+f"(d[91]), "+f"(d[92]), "+f"(d[93]), "+f"(d[94]), "+f"(d[95])
    : "r"(a0), "r"(a1), "r"(a2), "r"(a3), "l"(descB), "r"(scaleD));
}

__device__ __forceinline__ void wgmma_m64n64k16_rs(float (&d)[32], uint32_t a0, uint32_t a1, uint32_t a2, uint32_t a3, uint64_t descB, int scaleD) {
  asm volatile("{\n.reg .pred p;\nsetp.ne.b32 p, %37, 0;\n"
    "wgmma.mma_async.sync.aligned.m64n64k16.f32.bf16.bf16 "
    "{%0, %1, %2, %3, %4, %5, %6, %7, %8, %9, %10, %11, %12, %13, %14, %15, %16, %17, %18, %19, %20, %21, %22, %23, %24, %25, %26, %27, %28, %29, %30, %31}, {%32, %33, %34, %35}, %36, p, 1, 1, 0;\n}\n"
    : "+f"(d[0]), "+f"(d[1]), "+f"(d[2]), "+f"(d[3]), "+f"(d[4]), "+f"(d[5]), "+f"(d[6]), "+f"(d[7]), "+f"(d[8]), "+f"(d[9]), "+f"(d[10]), "+f"(d[11]), "+f"(d[12]), "+f"(d[13]), "+f"(d[14]), "+f"(d[15]), "+f"(d[16]), "+f"(d[17]), "+f"(d[18]), "+f"(d[19]), "+f"(d[20]), "+f"(d[21]), "+f"(d[22]), "+f"(d[23]), "+f"(d[24]), "+f"(d[25]), "+f"(d[26]), "+f"(d[27]), "+f"(d[28]), "+f"(d[29]), "+f"(d[30]), "+f"(d[31])
    : "r"(a0), "r"(a1), "r"(a2), "r"(a3), "l"(descB), "r"(scaleD));
}

__device__ __forceinline__ void wgmma_m64n56k16_rs(float (&d)[28], uint32_t a0, uint32_t a1, uint32_t a2, uint32_t a3, uint64_t descB, int scaleD) {
  asm volatile("{\n.reg .pred p;\nsetp.ne.b32 p, %33, 0;\n"
    "wgmma.mma_async.sync.aligned.m64n56k16.f32.bf16.bf16 "
    "{%0, %1, %2, %3, %4, %5, %6, %7, %8, %9, %10, %11, %12, %13, %14, %15, %16, %17, %18, %19, %20, %21, %22, %23, %24, %25, %26, %27}, {%28, %29, %30, %31}, %32, p, 1, 1, 0;\n}\n"
    : "+f"(d[0]), "+f"(d[1]), "+f"(d[2]), "+f"(d[3]), "+f"(d[4]), "+f"(d[5]), "+f"(d[6]), "+f"(d[7]), "+f"(d[8]), "+f"(d[9]), "+f"(d[10]), "+f"(d[11]), "+f"(d[12]), "+f"(d[13]), "+f"(d[14]), "+f"(d[15]), "+f"(d[16]), "+f"(d[17]), "+f"(d[18]), "+f"(d[19]), "+f"(d[20]), "+f"(d[21]), "+f"(d[22]), "+f"(d[23]), "+f"(d[24]), "+f"(d[25]), "+f"(d[26]), "+f"(d[27])
    : "r"(a0), "r"(a1), "r"(a2), "r"(a3), "l"(descB), "r"(scaleD));
}

__global__ void __launch_bounds__(256) merge_weights_kernel(const __nv_bfloat16* __restrict__ wqkv_t,
                                                            const __nv_bfloat16* __restrict__ wo_t,
                                                            const __nv_bfloat16* __restrict__ wqkv_s,
                                                            const __nv_bfloat16* __restrict__ wo_s) {
  __shared__ __nv_bfloat16 sA[32][196];
  __shared__ __nv_bfloat16 sB[32][196];
  int b = blockIdx.x;
  int mat = b / 36;
  int kt = (b % 36) / 6, nt = b % 6;
  const __nv_bfloat16* wqkv = (mat < 2) ? wqkv_t : wqkv_s;
  const __nv_bfloat16* wo = (mat < 2) ? wo_t : wo_s;
  bool isU = mat & 1;
  int tid = threadIdx.x;
  for (int i = tid; i < 32 * 192; i += 256) {
    int r = i / 192, d = i % 192;
    sA[r][d] = wqkv[(kt * 32 + r) * 576 + (isU ? 384 : 0) + d];
  }
  if (!isU) {
    for (int i = tid; i < 32 * 192; i += 256) {
      int r = i / 192, d = i % 192;
      sB[r][d] = wqkv[(nt * 32 + r) * 576 + 192 + d];
    }
  } else {
    for (int i = tid; i < 32 * 192; i += 256) {
      int d = i / 32, r = i % 32;
      sB[r][d] = wo[d * 192 + nt * 32 + r];
    }
  }
  __syncthreads();
  int kr = tid / 8;
  int n0 = (tid % 8) * 4;
  float acc[4] = {0.f, 0.f, 0.f, 0.f};
#pragma unroll 4
  for (int d = 0; d < 192; d++) {
    float a = __bfloat162float(sA[kr][d]);
#pragma unroll
    for (int j = 0; j < 4; j++) acc[j] = fmaf(a, __bfloat162float(sB[n0 + j][d]), acc[j]);
  }
  unsigned char* img = g_wimg[mat >> 1][mat & 1];
  int k = kt * 32 + kr;
#pragma unroll
  for (int j = 0; j < 4; j++) {
    int n = nt * 32 + n0 + j;
    size_t off = (size_t)(k / 64) * WBLK_BYTES + (size_t)n * 128 + (size_t)((((k % 64) / 8) ^ (n % 8)) * 16) + (k % 8) * 2;
    *reinterpret_cast<__nv_bfloat16*>(img + off) = __float2bfloat16(acc[j]);
  }
}

template <int STAGE>
__global__ void __launch_bounds__(512, 1) stage_kernel(const __grid_constant__ CUtensorMap map_in,
                                                       __nv_bfloat16* __restrict__ out) {
  extern __shared__ unsigned char smem_raw[];
  const uint32_t sbase = (smem_u32(smem_raw) + 1023u) & ~1023u;
  const int tid = threadIdx.x;
  const int warp = tid >> 5, lane = tid & 31;
  const int NT = (STAGE == 1) ? NT1 : NT2;
  const uint32_t bar_full = sbase + SM_BAR;
  const uint32_t bar_ready = bar_full + 8 * NSLOT;
  const uint32_t bar_out = bar_ready + 8 * NSLOT;
  const uint32_t bar_free = bar_out + 8 * NSLOT;
  const uint32_t bar_w = bar_free + 8 * NSLOT;

  if (tid == 0) {
    for (int s = 0; s < NSLOT; s++) {
      mbar_init(bar_full + 8 * s, 1);
      mbar_init(bar_ready + 8 * s, 8);
      mbar_init(bar_out + 8 * s, 4);
      mbar_init(bar_free + 8 * s, 8);
    }
    mbar_init(bar_w, 1);
    asm volatile("fence.mbarrier_init.release.cluster;" ::: "memory");
  }
  if (STAGE == 2) {
    for (int i = tid; i < NSLOT * 3 * 15 * 8; i += 512) {
      int s = i / 360, r = i % 360;
      int blk = r / 120, rr = r % 120;
      uint32_t addr = sbase + SM_SLOT + s * SLOT_BYTES + blk * BLK_BYTES + (49 + rr / 8) * 128 + (rr % 8) * 16;
      sts_u4(addr, make_uint4(0, 0, 0, 0));
    }
    fence_proxy_async();
  }
  __syncthreads();

  const int ntiles = (NT - (int)blockIdx.x + (int)gridDim.x - 1) / (int)gridDim.x;

  if (warp >= 8) {
    asm volatile("setmaxnreg.dec.sync.aligned.u32 48;");
    const int pw = warp - 8;
    const int sq4 = lane & 3;

    auto issue_load = [&](int i) {
      const int slot = i % NSLOT;
      const uint32_t sl = sbase + SM_SLOT + slot * SLOT_BYTES;
      const int tile = blockIdx.x + i * gridDim.x;
      if (STAGE == 1) {
        mbar_expect_tx(bar_full + 8 * slot, 3 * BLK_BYTES);
        for (int cb = 0; cb < 3; cb++) tma_load_3d(sl + cb * BLK_BYTES, &map_in, cb * 64, 0, tile * 16, bar_full + 8 * slot);
      } else {
        const int t = tile >> 10, wh = (tile >> 5) & 31, ww = tile & 31;
        mbar_expect_tx(bar_full + 8 * slot, 3 * 49 * 128);
        for (int cb = 0; cb < 3; cb++) tma_load_4d(sl + cb * BLK_BYTES, &map_in, cb * 64, ww * 7, wh * 7, t, bar_full + 8 * slot);
      }
    };
    auto prefetch = [&](int k) {
      if (k < ntiles) {
        const int tp = blockIdx.x + k * gridDim.x;
        if (STAGE == 1) {
          for (int cb = 0; cb < 3; cb++) tma_prefetch_3d(&map_in, cb * 64, 0, tp * 16);
        } else {
          const int t = tp >> 10, wh = (tp >> 5) & 31, ww = tp & 31;
          for (int cb = 0; cb < 3; cb++) tma_prefetch_4d(&map_in, cb * 64, ww * 7, wh * 7, t);
        }
      }
    };
    auto do_stats = [&](int i) {
      const int slot = i % NSLOT;
      const uint32_t par = (i / NSLOT) & 1;
      const uint32_t sl = sbase + SM_SLOT + slot * SLOT_BYTES;
      mbar_wait(bar_full + 8 * slot, par);
      {
        const int srow = pw * 8 + (lane >> 2);
        const uint32_t rbase = sl + srow * 128;
        const uint32_t sx = (uint32_t)((srow & 7) << 4);
        float a0 = 0.f, a1 = 0.f, a2 = 0.f, a3 = 0.f, b0 = 0.f, b1 = 0.f, b2 = 0.f, b3 = 0.f;
        float pivot = 0.f;
#pragma unroll
        for (int hh = 0; hh < 2; hh++) {
          uint4 v[3];
#pragma unroll
          for (int c = 0; c < 3; c++) {
            const uint32_t chunk = sq4 * 6 + hh * 3 + c;
            v[c] = lds_u4(rbase + (chunk >> 3) * BLK_BYTES + (((chunk & 7) << 4) ^ sx));
          }
          if (hh == 0) pivot = bf_lo(__shfl_sync(0xffffffffu, v[0].x, lane & ~3));
#pragma unroll
          for (int c = 0; c < 3; c++) {
            float d0 = bf_lo(v[c].x) - pivot, d1 = bf_hi(v[c].x) - pivot, d2 = bf_lo(v[c].y) - pivot, d3 = bf_hi(v[c].y) - pivot;
            float d4 = bf_lo(v[c].z) - pivot, d5 = bf_hi(v[c].z) - pivot, d6 = bf_lo(v[c].w) - pivot, d7 = bf_hi(v[c].w) - pivot;
            a0 += d0 + d4; a1 += d1 + d5; a2 += d2 + d6; a3 += d3 + d7;
            b0 = fmaf(d0, d0, b0); b1 = fmaf(d1, d1, b1); b2 = fmaf(d2, d2, b2); b3 = fmaf(d3, d3, b3);
            b0 = fmaf(d4, d4, b0); b1 = fmaf(d5, d5, b1); b2 = fmaf(d6, d6, b2); b3 = fmaf(d7, d7, b3);
          }
        }
        float s1 = (a0 + a1) + (a2 + a3), s2 = (b0 + b1) + (b2 + b3);
        s1 += __shfl_xor_sync(0xffffffffu, s1, 1);
        s2 += __shfl_xor_sync(0xffffffffu, s2, 1);
        s1 += __shfl_xor_sync(0xffffffffu, s1, 2);
        s2 += __shfl_xor_sync(0xffffffffu, s2, 2);
        const float dm = s1 * (1.0f / 192.0f);
        const float mean = pivot + dm;
        const float var = fmaxf(fmaf(-dm, dm, s2 * (1.0f / 192.0f)), 0.f);
        const float rstd = rsqrtf(var + 1e-5f);
        if (sq4 == 0) {
          const float SC = 0.07216878364870322f * 1.4426950408889634f;
          float a = rstd * SC;
          sts_f4(sbase + SM_STATS + slot * 1024 + srow * 16, make_float4(rstd, mean, a, a * mean));
        }
      }
      __syncwarp();
      if (lane == 0) mbar_arrive(bar_ready + 8 * slot);
    };

    if (pw == 0 && lane == 0) {
      mbar_expect_tx(bar_w, 2 * WMAT_BYTES);
      const unsigned char* src = g_wimg[STAGE - 1][0];
      for (int i = 0; i < 6; i++) bulk_load(sbase + SM_WM + i * WBLK_BYTES, src + i * WBLK_BYTES, WBLK_BYTES, bar_w);
      for (int i = 0; i < NSLOT && i < ntiles; i++) issue_load(i);
      for (int k = NSLOT; k < NSLOT + 2; k++) prefetch(k);
    }
    __syncwarp();
    for (int i = 0; i < NSLOT && i < ntiles; i++) do_stats(i);

    for (int k = 0; k < ntiles; k++) {
      const int slot = k % NSLOT;
      const uint32_t sl = sbase + SM_SLOT + slot * SLOT_BYTES;
      const int tile = blockIdx.x + k * gridDim.x;
      mbar_wait(bar_out + 8 * slot, (k / NSLOT) & 1);
#pragma unroll
      for (int rg = 0; rg < 2; rg++) {
        const int row = 8 * pw + 4 * rg + (lane >> 3);
        __nv_bfloat16* orow;
        bool valid = true;
        if (STAGE == 1) {
          orow = out + ((size_t)(row & 3) * HW_DIM + (size_t)tile * 16 + (row >> 2)) * C_DIM;
        } else {
          const int t = tile >> 10, wh = (tile >> 5) & 31, ww = tile & 31;
          const int rh = row / 7;
          orow = out + ((size_t)t * HW_DIM + (size_t)(wh * 7 + rh) * 224 + ww * 7 + (row - rh * 7)) * C_DIM;
          valid = row < 49;
        }
        const uint32_t rb = sl + row * 128 + ((((lane & 7) ^ (row & 7))) << 4);
        uint4 v0 = lds_u4(rb), v1 = lds_u4(rb + BLK_BYTES), v2 = lds_u4(rb + 2 * BLK_BYTES);
        if (valid) {
          *reinterpret_cast<uint4*>(orow + (lane & 7) * 8) = v0;
          *reinterpret_cast<uint4*>(orow + 64 + (lane & 7) * 8) = v1;
          *reinterpret_cast<uint4*>(orow + 128 + (lane & 7) * 8) = v2;
        }
      }
      __syncwarp();
      if (lane == 0) mbar_arrive(bar_free + 8 * slot);
      if (k + NSLOT < ntiles) {
        if (pw == 0 && lane == 0) {
          mbar_wait(bar_free + 8 * slot, (k / NSLOT) & 1);
          issue_load(k + NSLOT);
          prefetch(k + NSLOT + 2);
        }
        __syncwarp();
        do_stats(k + NSLOT);
      }
    }
  } else {
    asm volatile("setmaxnreg.inc.sync.aligned.u32 208;");
    const int wg = warp >> 2;
    const int w = warp & 3;
    const int q = lane & 3, r = lane >> 2;
    const int row0 = 16 * w + r, row1 = row0 + 8;

    mbar_wait(bar_w, 0);
    if (tid < 192) {
      float s = 0.f;
      const uint32_t rowb = sbase + SM_WM + tid * 128;
#pragma unroll
      for (int kb = 0; kb < 3; kb++)
#pragma unroll
        for (int c = 0; c < 8; c++) {
          uint4 v = lds_u4(rowb + kb * WBLK_BYTES + ((c ^ (tid & 7)) << 4));
          s += (bf_lo(v.x) + bf_hi(v.x)) + (bf_lo(v.y) + bf_hi(v.y)) + (bf_lo(v.z) + bf_hi(v.z)) + (bf_lo(v.w) + bf_hi(v.w));
        }
      sts_f32(sbase + SM_MSUM + tid * 4, s);
    }
    named_bar_sync(3, 256);

    const uint64_t dW_M = make_desc(sbase + SM_WM, 16, 1024);
    const uint64_t dW_U = make_desc(sbase + SM_WU, 16, 1024);

    for (int i = wg; i < ntiles; i += 2) {
      const int slot = i % NSLOT;
      const uint32_t par = (i / NSLOT) & 1;
      const uint32_t sl = sbase + SM_SLOT + slot * SLOT_BYTES;
      const uint32_t st = sbase + SM_STATS + slot * 1024;
      const uint64_t dX = make_desc(sl, 16, 1024);

      float acc[96];
      uint32_t pk[48];
      TL(0);
      mbar_wait(bar_full + 8 * slot, par);
      TL(1);
      wg_fence();
#pragma unroll
      for (int kb = 0; kb < 3; kb++)
#pragma unroll
        for (int kk = 0; kk < 4; kk++)
          wgmma_m64n192k16_ss(acc, dX + ((kb * BLK_BYTES + kk * 32) >> 4), dW_M + ((kb * WBLK_BYTES + kk * 32) >> 4),
                              (kb | kk) != 0);
      wg_commit();
      TL(2);
      mbar_wait(bar_ready + 8 * slot, par);
      TL(3);
      const float4 st0 = lds_f4(st + row0 * 16), st1 = lds_f4(st + row1 * 16);
      float2 msv[24];
#pragma unroll
      for (int j = 0; j < 24; j++) msv[j] = lds_f2(sbase + SM_MSUM + (8 * j + 2 * q) * 4);
      wg_wait0();
      fence_regs(acc);
      TL(4);
      float gsum0 = 0.f, gsum1 = 0.f;
      {
        const float rs0 = st0.x, mr0 = st0.x * st0.y, rs1 = st1.x, mr1 = st1.x * st1.y;
#pragma unroll
        for (int j = 0; j < 24; j++) {
          const float2 ms = msv[j];
          float g00 = fmaf(acc[4 * j + 0], rs0, -mr0 * ms.x);
          float g01 = fmaf(acc[4 * j + 1], rs0, -mr0 * ms.y);
          float g10 = fmaf(acc[4 * j + 2], rs1, -mr1 * ms.x);
          float g11 = fmaf(acc[4 * j + 3], rs1, -mr1 * ms.y);
          uint32_t p0 = pack_bf16(g00, g01), p1 = pack_bf16(g10, g11);
          pk[2 * j] = p0;
          pk[2 * j + 1] = p1;
          gsum0 += bf_lo(p0) + bf_hi(p0);
          gsum1 += bf_lo(p1) + bf_hi(p1);
        }
      }
      TL(5);
      float sacc[32];
      wg_fence();
#pragma unroll
      for (int kb = 0; kb < 3; kb++)
#pragma unroll
        for (int kk = 0; kk < 4; kk++) {
          const int s = kb * 4 + kk;
          wgmma_m64n64k16_rs(sacc, pk[4 * s + 0], pk[4 * s + 1], pk[4 * s + 2], pk[4 * s + 3],
                             dX + ((kb * BLK_BYTES + kk * 32) >> 4), s != 0);
        }
      wg_commit();
      gsum0 += __shfl_xor_sync(0xffffffffu, gsum0, 1);
      gsum0 += __shfl_xor_sync(0xffffffffu, gsum0, 2);
      gsum1 += __shfl_xor_sync(0xffffffffu, gsum1, 1);
      gsum1 += __shfl_xor_sync(0xffffffffu, gsum1, 2);
      float4 kp[16];
#pragma unroll
      for (int jj = 0; jj < 8; jj++) {
        kp[2 * jj] = lds_f4(st + (8 * jj + 2 * q) * 16);
        kp[2 * jj + 1] = lds_f4(st + (8 * jj + 2 * q + 1) * 16);
      }
      wg_wait0();
      fence_regs(sacc);
      TL(6);
      uint32_t pf[16];
      float linv0, linv1, cc0, cc1;
      {
        float sv[32];
        float mx0 = -INFINITY, mx1 = -INFINITY;
#pragma unroll
        for (int jj = 0; jj < 8; jj++) {
          const int j0 = 8 * jj + 2 * q;
          const float4 k0 = kp[2 * jj], k1 = kp[2 * jj + 1];
          float s00 = fmaf(k0.z, sacc[4 * jj + 0], -k0.w * gsum0);
          float s01 = fmaf(k1.z, sacc[4 * jj + 1], -k1.w * gsum0);
          float s10 = fmaf(k0.z, sacc[4 * jj + 2], -k0.w * gsum1);
          float s11 = fmaf(k1.z, sacc[4 * jj + 3], -k1.w * gsum1);
          bool v00, v01, v10, v11;
          if (STAGE == 1) {
            v00 = (j0 >> 2) == (row0 >> 2);
            v01 = ((j0 + 1) >> 2) == (row0 >> 2);
            v10 = (j0 >> 2) == (row1 >> 2);
            v11 = ((j0 + 1) >> 2) == (row1 >> 2);
          } else {
            v00 = v10 = j0 < 49;
            v01 = v11 = (j0 + 1) < 49;
          }
          s00 = v00 ? s00 : -INFINITY;
          s01 = v01 ? s01 : -INFINITY;
          s10 = v10 ? s10 : -INFINITY;
          s11 = v11 ? s11 : -INFINITY;
          sv[4 * jj + 0] = s00; sv[4 * jj + 1] = s01; sv[4 * jj + 2] = s10; sv[4 * jj + 3] = s11;
          mx0 = fmaxf(mx0, fmaxf(s00, s01));
          mx1 = fmaxf(mx1, fmaxf(s10, s11));
        }
        mx0 = fmaxf(mx0, __shfl_xor_sync(0xffffffffu, mx0, 1));
        mx0 = fmaxf(mx0, __shfl_xor_sync(0xffffffffu, mx0, 2));
        mx1 = fmaxf(mx1, __shfl_xor_sync(0xffffffffu, mx1, 1));
        mx1 = fmaxf(mx1, __shfl_xor_sync(0xffffffffu, mx1, 2));
        float l0 = 0.f, l1 = 0.f;
        cc0 = 0.f; cc1 = 0.f;
#pragma unroll
        for (int jj = 0; jj < 8; jj++) {
          const int j0 = 8 * jj + 2 * q;
          const float4 k0 = kp[2 * jj], k1 = kp[2 * jj + 1];
          float p00 = ex2(sv[4 * jj + 0] - mx0), p01 = ex2(sv[4 * jj + 1] - mx0);
          float p10 = ex2(sv[4 * jj + 2] - mx1), p11 = ex2(sv[4 * jj + 3] - mx1);
          l0 += p00 + p01;
          l1 += p10 + p11;
          uint32_t f0 = pack_bf16(p00 * k0.x, p01 * k1.x);
          uint32_t f1 = pack_bf16(p10 * k0.x, p11 * k1.x);
          cc0 = fmaf(bf_lo(f0), k0.y, fmaf(bf_hi(f0), k1.y, cc0));
          cc1 = fmaf(bf_lo(f1), k0.y, fmaf(bf_hi(f1), k1.y, cc1));
          pf[2 * jj] = f0;
          pf[2 * jj + 1] = f1;
        }
        l0 += __shfl_xor_sync(0xffffffffu, l0, 1);
        l0 += __shfl_xor_sync(0xffffffffu, l0, 2);
        l1 += __shfl_xor_sync(0xffffffffu, l1, 1);
        l1 += __shfl_xor_sync(0xffffffffu, l1, 2);
        cc0 += __shfl_xor_sync(0xffffffffu, cc0, 1);
        cc0 += __shfl_xor_sync(0xffffffffu, cc0, 2);
        cc1 += __shfl_xor_sync(0xffffffffu, cc1, 1);
        cc1 += __shfl_xor_sync(0xffffffffu, cc1, 2);
        linv0 = 1.0f / l0;
        linv1 = 1.0f / l1;
      }
      TL(7);
      {
        const uint64_t dXt = make_desc(sl, BLK_BYTES, 1024);
        wg_fence();
#pragma unroll
        for (int s = 0; s < 4; s++)
          wgmma_m64n192k16_rs_tb(acc, pf[4 * s + 0], pf[4 * s + 1], pf[4 * s + 2], pf[4 * s + 3], dXt + ((s * 2048) >> 4),
                                 s != 0);
        wg_commit();
        wg_wait0();
        fence_regs(acc);
      }
      TL(8);
#pragma unroll
      for (int j = 0; j < 24; j++) {
        pk[2 * j] = pack_bf16((acc[4 * j + 0] - cc0) * linv0, (acc[4 * j + 1] - cc0) * linv0);
        pk[2 * j + 1] = pack_bf16((acc[4 * j + 2] - cc1) * linv1, (acc[4 * j + 3] - cc1) * linv1);
      }
      TL(9);
      wg_fence();
#pragma unroll
      for (int kb = 0; kb < 3; kb++)
#pragma unroll
        for (int kk = 0; kk < 4; kk++) {
          const int s = kb * 4 + kk;
          wgmma_m64n192k16_rs(acc, pk[4 * s + 0], pk[4 * s + 1], pk[4 * s + 2], pk[4 * s + 3],
                              dW_U + ((kb * WBLK_BYTES + kk * 32) >> 4), s != 0);
        }
      wg_commit();
      wg_wait0();
      fence_regs(acc);
      TL(10);
      {
        const int mrow = 16 * w + ((lane >> 3) & 1) * 8 + (lane & 7);
        const uint32_t abase = sl + mrow * 128;
#pragma unroll
        for (int j = 0; j < 24; j += 2) {
          const int chunk = j + (lane >> 4);
          const uint32_t addr = abase + (chunk >> 3) * BLK_BYTES + (((chunk & 7) ^ (lane & 7)) << 4);
          ldsm_x4(addr, pk[2 * j], pk[2 * j + 1], pk[2 * j + 2], pk[2 * j + 3]);
        }
#pragma unroll
        for (int j = 0; j < 24; j++) {
          pk[2 * j] = pack_bf16(acc[4 * j + 0] + bf_lo(pk[2 * j]), acc[4 * j + 1] + bf_hi(pk[2 * j]));
          pk[2 * j + 1] = pack_bf16(acc[4 * j + 2] + bf_lo(pk[2 * j + 1]), acc[4 * j + 3] + bf_hi(pk[2 * j + 1]));
        }
#pragma unroll
        for (int j = 0; j < 24; j += 2) {
          const int chunk = j + (lane >> 4);
          const uint32_t addr = abase + (chunk >> 3) * BLK_BYTES + (((chunk & 7) ^ (lane & 7)) << 4);
          stsm_x4(addr, pk[2 * j], pk[2 * j + 1], pk[2 * j + 2], pk[2 * j + 3]);
        }
        __syncwarp();
        if (lane == 0) mbar_arrive(bar_out + 8 * slot);
      }
      TL(11);
    }
  }
}

typedef CUresult (*PFN_encodeTiled)(CUtensorMap*, CUtensorMapDataType, cuuint32_t, void*, const cuuint64_t*, const cuuint64_t*,
                                    const cuuint32_t*, const cuuint32_t*, CUtensorMapInterleave, CUtensorMapSwizzle,
                                    CUtensorMapL2promotion, CUtensorMapFloatOOBfill);

static PFN_encodeTiled get_encode() {
  static PFN_encodeTiled fn = nullptr;
  if (!fn) {
    void* p = nullptr;
    cudaDriverEntryPointQueryResult qres;
    cudaGetDriverEntryPoint("cuTensorMapEncodeTiled", &p, cudaEnableDefault, &qres);
    fn = (PFN_encodeTiled)p;
  }
  return fn;
}

extern "C" void kernel_launch(void* const* d_in, const int* in_sizes, int n_in, void* d_out, int out_size) {
  (void)in_sizes; (void)n_in; (void)out_size;
  const __nv_bfloat16* x = (const __nv_bfloat16*)d_in[0];
  const __nv_bfloat16* wqkv_t = (const __nv_bfloat16*)d_in[1];
  const __nv_bfloat16* wo_t = (const __nv_bfloat16*)d_in[2];
  const __nv_bfloat16* wqkv_s = (const __nv_bfloat16*)d_in[3];
  const __nv_bfloat16* wo_s = (const __nv_bfloat16*)d_in[4];
  PFN_encodeTiled enc = get_encode();

  CUtensorMap m1_in, m1_out, m2;
  {
    cuuint64_t dims[3] = {192, 4, 50176};
    cuuint64_t strides[2] = {(cuuint64_t)HW_DIM * 384, 384};
    cuuint32_t box[3] = {64, 4, 16};
    cuuint32_t es[3] = {1, 1, 1};
    enc(&m1_in, CU_TENSOR_MAP_DATA_TYPE_BFLOAT16, 3, (void*)x, dims, strides, box, es, CU_TENSOR_MAP_INTERLEAVE_NONE,
        CU_TENSOR_MAP_SWIZZLE_128B, CU_TENSOR_MAP_L2_PROMOTION_L2_256B, CU_TENSOR_MAP_FLOAT_OOB_FILL_NONE);
    enc(&m1_out, CU_TENSOR_MAP_DATA_TYPE_BFLOAT16, 3, d_out, dims, strides, box, es, CU_TENSOR_MAP_INTERLEAVE_NONE,
        CU_TENSOR_MAP_SWIZZLE_128B, CU_TENSOR_MAP_L2_PROMOTION_L2_256B, CU_TENSOR_MAP_FLOAT_OOB_FILL_NONE);
  }
  {
    cuuint64_t dims[4] = {192, 224, 224, 4};
    cuuint64_t strides[3] = {384, 224 * 384, (cuuint64_t)HW_DIM * 384};
    cuuint32_t box[4] = {64, 7, 7, 1};
    cuuint32_t es[4] = {1, 1, 1, 1};
    enc(&m2, CU_TENSOR_MAP_DATA_TYPE_BFLOAT16, 4, d_out, dims, strides, box, es, CU_TENSOR_MAP_INTERLEAVE_NONE,
        CU_TENSOR_MAP_SWIZZLE_128B, CU_TENSOR_MAP_L2_PROMOTION_L2_256B, CU_TENSOR_MAP_FLOAT_OOB_FILL_NONE);
  }
  const int smem = SM_TOTAL + 1024;
  cudaFuncSetAttribute(stage_kernel<1>, cudaFuncAttributeMaxDynamicSharedMemorySize, smem);
  cudaFuncSetAttribute(stage_kernel<2>, cudaFuncAttributeMaxDynamicSharedMemorySize, smem);
  int nsm = 132;
  cudaDeviceGetAttribute(&nsm, cudaDevAttrMultiProcessorCount, 0);

  merge_weights_kernel<<<144, 256>>>(wqkv_t, wo_t, wqkv_s, wo_s);
  stage_kernel<1><<<nsm, 512, smem>>>(m1_in, (__nv_bfloat16*)d_out);
  stage_kernel<2><<<nsm, 512, smem>>>(m2, (__nv_bfloat16*)d_out);
}
```

```cpp
#include <cuda_runtime.h>
#include <cuda_bf16.h>
#include <cuda.h>
#include <stdint.h>

#define C_DIM 192
#define T_DIM 4
#define HW_DIM 50176
#define NT1 3136
#define NT2 4096

#define SLOT_BYTES 24576
#define BLK_BYTES 8192
#define WMAT_BYTES 73728
#define WBLK_BYTES 24576
#define NSLOT 3

#define SM_WM 0
#define SM_WU WMAT_BYTES
#define SM_SLOT (2 * WMAT_BYTES)
#define SM_STATS (SM_SLOT + NSLOT * SLOT_BYTES)
#define SM_MSUM (SM_STATS + NSLOT * 1024)
#define SM_BAR (SM_MSUM + 768)
#define SM_TOTAL (SM_BAR + 256)

__device__ __align__(1024) unsigned char g_wimg[2][2][WMAT_BYTES];
#define TL(idx)
#define TLP(idx)

__device__ __forceinline__ uint32_t smem_u32(const void* p) { return (uint32_t)__cvta_generic_to_shared(p); }

__device__ __forceinline__ void mbar_init(uint32_t bar, uint32_t count) {
  asm volatile("mbarrier.init.shared::cta.b64 [%0], %1;" ::"r"(bar), "r"(count) : "memory");
}
__device__ __forceinline__ void mbar_expect_tx(uint32_t bar, uint32_t bytes) {
  asm volatile("mbarrier.arrive.expect_tx.shared::cta.b64 _, [%0], %1;" ::"r"(bar), "r"(bytes) : "memory");
}
__device__ __forceinline__ void mbar_arrive(uint32_t bar) {
  asm volatile("mbarrier.arrive.shared::cta.b64 _, [%0];" ::"r"(bar) : "memory");
}
__device__ __forceinline__ bool mbar_try_wait(uint32_t bar, uint32_t parity) {
  uint32_t ok;
  asm volatile(
      "{\n.reg .pred p;\nmbarrier.try_wait.parity.shared::cta.b64 p, [%1], %2;\nselp.u32 %0, 1, 0, p;\n}\n"
      : "=r"(ok)
      : "r"(bar), "r"(parity)
      : "memory");
  return ok != 0;
}
__device__ __forceinline__ void mbar_wait(uint32_t bar, uint32_t parity) {
  for (uint32_t it = 0; it < (1u << 24); ++it)
    if (mbar_try_wait(bar, parity)) break;
}
__device__ __forceinline__ void fence_proxy_async() { asm volatile("fence.proxy.async.shared::cta;" ::: "memory"); }
__device__ __forceinline__ void named_bar_sync(int id, int nthreads) {
  asm volatile("bar.sync %0, %1;" ::"r"(id), "r"(nthreads) : "memory");
}

__device__ __forceinline__ void tma_load_3d(uint32_t dst, const CUtensorMap* map, int c0, int c1, int c2, uint32_t bar) {
  asm volatile(
      "cp.async.bulk.tensor.3d.shared::cluster.global.mbarrier::complete_tx::bytes [%0], [%1, {%3, %4, %5}], [%2];"
      ::"r"(dst), "l"(map), "r"(bar), "r"(c0), "r"(c1), "r"(c2) : "memory");
}
__device__ __forceinline__ void tma_load_4d(uint32_t dst, const CUtensorMap* map, int c0, int c1, int c2, int c3, uint32_t bar) {
  asm volatile(
      "cp.async.bulk.tensor.4d.shared::cluster.global.mbarrier::complete_tx::bytes [%0], [%1, {%3, %4, %5, %6}], [%2];"
      ::"r"(dst), "l"(map), "r"(bar), "r"(c0), "r"(c1), "r"(c2), "r"(c3) : "memory");
}
__device__ __forceinline__ void tma_store_3d(const CUtensorMap* map, uint32_t src, int c0, int c1, int c2) {
  asm volatile("cp.async.bulk.tensor.3d.global.shared::cta.bulk_group [%0, {%2, %3, %4}], [%1];"
               ::"l"(map), "r"(src), "r"(c0), "r"(c1), "r"(c2) : "memory");
}
__device__ __forceinline__ void tma_store_4d(const CUtensorMap* map, uint32_t src, int c0, int c1, int c2, int c3) {
  asm volatile("cp.async.bulk.tensor.4d.global.shared::cta.bulk_group [%0, {%2, %3, %4, %5}], [%1];"
               ::"l"(map), "r"(src), "r"(c0), "r"(c1), "r"(c2), "r"(c3) : "memory");
}
__device__ __forceinline__ void tma_prefetch_3d(const CUtensorMap* map, int c0, int c1, int c2) {
  asm volatile("cp.async.bulk.prefetch.tensor.3d.L2.global.tile [%0, {%1, %2, %3}];" ::"l"(map), "r"(c0), "r"(c1), "r"(c2) : "memory");
}
__device__ __forceinline__ void tma_prefetch_4d(const CUtensorMap* map, int c0, int c1, int c2, int c3) {
  asm volatile("cp.async.bulk.prefetch.tensor.4d.L2.global.tile [%0, {%1, %2, %3, %4}];" ::"l"(map), "r"(c0), "r"(c1), "r"(c2), "r"(c3) : "memory");
}
__device__ __forceinline__ void bulk_commit() { asm volatile("cp.async.bulk.commit_group;" ::: "memory"); }
__device__ __forceinline__ void bulk_wait_read0() { asm volatile("cp.async.bulk.wait_group.read 0;" ::: "memory"); }
__device__ __forceinline__ void bulk_wait0() { asm volatile("cp.async.bulk.wait_group 0;" ::: "memory"); }
__device__ __forceinline__ void bulk_load(uint32_t dst, const void* src, uint32_t bytes, uint32_t bar) {
  asm volatile("cp.async.bulk.shared::cluster.global.mbarrier::complete_tx::bytes [%0], [%1], %2, [%3];"
               ::"r"(dst), "l"(src), "r"(bytes), "r"(bar) : "memory");
}

__device__ __forceinline__ void wg_fence() { asm volatile("wgmma.fence.sync.aligned;" ::: "memory"); }
__device__ __forceinline__ void wg_commit() { asm volatile("wgmma.commit_group.sync.aligned;" ::: "memory"); }
__device__ __forceinline__ void wg_wait0() { asm volatile("wgmma.wait_group.sync.aligned 0;" ::: "memory"); }
template <int N>
__device__ __forceinline__ void fence_regs(float (&d)[N]) {
#pragma unroll
  for (int i = 0; i < N; i++) asm volatile("" : "+f"(d[i])::"memory");
}

__device__ __forceinline__ uint64_t make_desc(uint32_t addr, uint32_t lbo, uint32_t sbo) {
  return (uint64_t)((addr & 0x3FFFF) >> 4) | ((uint64_t)(lbo >> 4) << 16) | ((uint64_t)(sbo >> 4) << 32) | (1ull << 62);
}

__device__ __forceinline__ uint32_t pack_bf16(float lo, float hi) {
  uint32_t r;
  asm("cvt.rn.bf16x2.f32 %0, %1, %2;" : "=r"(r) : "f"(hi), "f"(lo));
  return r;
}
__device__ __forceinline__ float bf_lo(uint32_t v) { return __uint_as_float(v << 16); }
__device__ __forceinline__ float bf_hi(uint32_t v) { return __uint_as_float(v & 0xffff0000u); }

__device__ __forceinline__ void ldsm_x4(uint32_t addr, uint32_t& r0, uint32_t& r1, uint32_t& r2, uint32_t& r3) {
  asm volatile("ldmatrix.sync.aligned.m8n8.x4.shared.b16 {%0, %1, %2, %3}, [%4];"
               : "=r"(r0), "=r"(r1), "=r"(r2), "=r"(r3) : "r"(addr) : "memory");
}
__device__ __forceinline__ void stsm_x4(uint32_t addr, uint32_t r0, uint32_t r1, uint32_t r2, uint32_t r3) {
  asm volatile("stmatrix.sync.aligned.m8n8.x4.shared.b16 [%0], {%1, %2, %3, %4};"
               ::"r"(addr), "r"(r0), "r"(r1), "r"(r2), "r"(r3) : "memory");
}
__device__ __forceinline__ float4 lds_f4(uint32_t addr) {
  float4 v;
  asm volatile("ld.shared.v4.f32 {%0, %1, %2, %3}, [%4];" : "=f"(v.x), "=f"(v.y), "=f"(v.z), "=f"(v.w) : "r"(addr));
  return v;
}
__device__ __forceinline__ float2 lds_f2(uint32_t addr) {
  float2 v;
  asm volatile("ld.shared.v2.f32 {%0, %1}, [%2];" : "=f"(v.x), "=f"(v.y) : "r"(addr));
  return v;
}
__device__ __forceinline__ uint4 lds_u4(uint32_t addr) {
  uint4 v;
  asm volatile("ld.shared.v4.u32 {%0, %1, %2, %3}, [%4];" : "=r"(v.x), "=r"(v.y), "=r"(v.z), "=r"(v.w) : "r"(addr));
  return v;
}
__device__ __forceinline__ void sts_f4(uint32_t addr, float4 v) {
  asm volatile("st.shared.v4.f32 [%0], {%1, %2, %3, %4};" ::"r"(addr), "f"(v.x), "f"(v.y), "f"(v.z), "f"(v.w) : "memory");
}
__device__ __forceinline__ void sts_u4(uint32_t addr, uint4 v) {
  asm volatile("st.shared.v4.u32 [%0], {%1, %2, %3, %4};" ::"r"(addr), "r"(v.x), "r"(v.y), "r"(v.z), "r"(v.w) : "memory");
}
__device__ __forceinline__ void sts_f32(uint32_t addr, float v) {
  asm volatile("st.shared.f32 [%0], %1;" ::"r"(addr), "f"(v) : "memory");
}
__device__ __forceinline__ float ex2(float x) {
  float y;
  asm("ex2.approx.ftz.f32 %0, %1;" : "=f"(y) : "f"(x));
  return y;
}

__device__ __forceinline__ void wgmma_m64n192k16_ss(float (&d)[96], uint64_t descA, uint64_t descB, int scaleD) {
  asm volatile("{\n.reg .pred p;\nsetp.ne.b32 p, %98, 0;\n"
    "wgmma.mma_async.sync.aligned.m64n192k16.f32.bf16.bf16 "
    "{%0, %1, %2, %3, %4, %5, %6, %7, %8, %9, %10, %11, %12, %13, %14, %15, %16, %17, %18, %19, %20, %21, %22, %23, %24, %25, %26, %27, %28, %29, %30, %31, %32, %33, %34, %35, %36, %37, %38, %39, %40, %41, %42, %43, %44, %45, %46, %47, %48, %49, %50, %51, %52, %53, %54, %55, %56, %57, %58, %59, %60, %61, %62, %63, %64, %65, %66, %67, %68, %69, %70, %71, %72, %73, %74, %75, %76, %77, %78, %79, %80, %81, %82, %83, %84, %85, %86, %87, %88, %89, %90, %91, %92, %93, %94, %95}, %96, %97, p, 1, 1, 0, 0;\n}\n"
    : "+f"(d[0]), "+f"(d[1]), "+f"(d[2]), "+f"(d[3]), "+f"(d[4]), "+f"(d[5]), "+f"(d[6]), "+f"(d[7]), "+f"(d[8]), "+f"(d[9]), "+f"(d[10]), "+f"(d[11]), "+f"(d[12]), "+f"(d[13]), "+f"(d[14]), "+f"(d[15]), "+f"(d[16]), "+f"(d[17]), "+f"(d[18]), "+f"(d[19]), "+f"(d[20]), "+f"(d[21]), "+f"(d[22]), "+f"(d[23]), "+f"(d[24]), "+f"(d[25]), "+f"(d[26]), "+f"(d[27]), "+f"(d[28]), "+f"(d[29]), "+f"(d[30]), "+f"(d[31]), "+f"(d[32]), "+f"(d[33]), "+f"(d[34]), "+f"(d[35]), "+f"(d[36]), "+f"(d[37]), "+f"(d[38]), "+f"(d[39]), "+f"(d[40]), "+f"(d[41]), "+f"(d[42]), "+f"(d[43]), "+f"(d[44]), "+f"(d[45]), "+f"(d[46]), "+f"(d[47]), "+f"(d[48]), "+f"(d[49]), "+f"(d[50]), "+f"(d[51]), "+f"(d[52]), "+f"(d[53]), "+f"(d[54]), "+f"(d[55]), "+f"(d[56]), "+f"(d[57]), "+f"(d[58]), "+f"(d[59]), "+f"(d[60]), "+f"(d[61]), "+f"(d[62]), "+f"(d[63]), "+f"(d[64]), "+f"(d[65]), "+f"(d[66]), "+f"(d[67]), "+f"(d[68]), "+f"(d[69]), "+f"(d[70]), "+f"(d[71]), "+f"(d[72]), "+f"(d[73]), "+f"(d[74]), "+f"(d[75]), "+f"(d[76]), "+f"(d[77]), "+f"(d[78]), "+f"(d[79]), "+f"(d[80]), "+f"(d[81]), "+f"(d[82]), "+f"(d[83]), "+f"(d[84]), "+f"(d[85]), "+f"(d[86]), "+f"(d[87]), "+f"(d[88]), "+f"(d[89]), "+f"(d[90]), "+f"(d[91]), "+f"(d[92]), "+f"(d[93]), "+f"(d[94]), "+f"(d[95])
    : "l"(descA), "l"(descB), "r"(scaleD));
}

__device__ __forceinline__ void wgmma_m64n192k16_rs(float (&d)[96], uint32_t a0, uint32_t a1, uint32_t a2, uint32_t a3, uint64_t descB, int scaleD) {
  asm volatile("{\n.reg .pred p;\nsetp.ne.b32 p, %101, 0;\n"
    "wgmma.mma_async.sync.aligned.m64n192k16.f32.bf16.bf16 "
    "{%0, %1, %2, %3, %4, %5, %6, %7, %8, %9, %10, %11, %12, %13, %14, %15, %16, %17, %18, %19, %20, %21, %22, %23, %24, %25, %26, %27, %28, %29, %30, %31, %32, %33, %34, %35, %36, %37, %38, %39, %40, %41, %42, %43, %44, %45, %46, %47, %48, %49, %50, %51, %52, %53, %54, %55, %56, %57, %58, %59, %60, %61, %62, %63, %64, %65, %66, %67, %68, %69, %70, %71, %72, %73, %74, %75, %76, %77, %78, %79, %80, %81, %82, %83, %84, %85, %86, %87, %88, %89, %90, %91, %92, %93, %94, %95}, {%96, %97, %98, %99}, %100, p, 1, 1, 0;\n}\n"
    : "+f"(d[0]), "+f"(d[1]), "+f"(d[2]), "+f"(d[3]), "+f"(d[4]), "+f"(d[5]), "+f"(d[6]), "+f"(d[7]), "+f"(d[8]), "+f"(d[9]), "+f"(d[10]), "+f"(d[11]), "+f"(d[12]), "+f"(d[13]), "+f"(d[14]), "+f"(d[15]), "+f"(d[16]), "+f"(d[17]), "+f"(d[18]), "+f"(d[19]), "+f"(d[20]), "+f"(d[21]), "+f"(d[22]), "+f"(d[23]), "+f"(d[24]), "+f"(d[25]), "+f"(d[26]), "+f"(d[27]), "+f"(d[28]), "+f"(d[29]), "+f"(d[30]), "+f"(d[31]), "+f"(d[32]), "+f"(d[33]), "+f"(d[34]), "+f"(d[35]), "+f"(d[36]), "+f"(d[37]), "+f"(d[38]), "+f"(d[39]), "+f"(d[40]), "+f"(d[41]), "+f"(d[42]), "+f"(d[43]), "+f"(d[44]), "+f"(d[45]), "+f"(d[46]), "+f"(d[47]), "+f"(d[48]), "+f"(d[49]), "+f"(d[50]), "+f"(d[51]), "+f"(d[52]), "+f"(d[53]), "+f"(d[54]), "+f"(d[55]), "+f"(d[56]), "+f"(d[57]), "+f"(d[58]), "+f"(d[59]), "+f"(d[60]), "+f"(d[61]), "+f"(d[62]), "+f"(d[63]), "+f"(d[64]), "+f"(d[65]), "+f"(d[66]), "+f"(d[67]), "+f"(d[68]), "+f"(d[69]), "+f"(d[70]), "+f"(d[71]), "+f"(d[72]), "+f"(d[73]), "+f"(d[74]), "+f"(d[75]), "+f"(d[76]), "+f"(d[77]), "+f"(d[78]), "+f"(d[79]), "+f"(d[80]), "+f"(d[81]), "+f"(d[82]), "+f"(d[83]), "+f"(d[84]), "+f"(d[85]), "+f"(d[86]), "+f"(d[87]), "+f"(d[88]), "+f"(d[89]), "+f"(d[90]), "+f"(d[91]), "+f"(d[92]), "+f"(d[93]), "+f"(d[94]), "+f"(d[95])
    : "r"(a0), "r"(a1), "r"(a2), "r"(a3), "l"(descB), "r"(scaleD));
}

__device__ __forceinline__ void wgmma_m64n192k16_rs_tb(float (&d)[96], uint32_t a0, uint32_t a1, uint32_t a2, uint32_t a3, uint64_t descB, int scaleD) {
  asm volatile("{\n.reg .pred p;\nsetp.ne.b32 p, %101, 0;\n"
    "wgmma.mma_async.sync.aligned.m64n192k16.f32.bf16.bf16 "
    "{%0, %1, %2, %3, %4, %5, %6, %7, %8, %9, %10, %11, %12, %13, %14, %15, %16, %17, %18, %19, %20, %21, %22, %23, %24, %25, %26, %27, %28, %29, %30, %31, %32, %33, %34, %35, %36, %37, %38, %39, %40, %41, %42, %43, %44, %45, %46, %47, %48, %49, %50, %51, %52, %53, %54, %55, %56, %57, %58, %59, %60, %61, %62, %63, %64, %65, %66, %67, %68, %69, %70, %71, %72, %73, %74, %75, %76, %77, %78, %79, %80, %81, %82, %83, %84, %85, %86, %87, %88, %89, %90, %91, %92, %93, %94, %95}, {%96, %97, %98, %99}, %100, p, 1, 1, 1;\n}\n"
    : "+f"(d[0]), "+f"(d[1]), "+f"(d[2]), "+f"(d[3]), "+f"(d[4]), "+f"(d[5]), "+f"(d[6]), "+f"(d[7]), "+f"(d[8]), "+f"(d[9]), "+f"(d[10]), "+f"(d[11]), "+f"(d[12]), "+f"(d[13]), "+f"(d[14]), "+f"(d[15]), "+f"(d[16]), "+f"(d[17]), "+f"(d[18]), "+f"(d[19]), "+f"(d[20]), "+f"(d[21]), "+f"(d[22]), "+f"(d[23]), "+f"(d[24]), "+f"(d[25]), "+f"(d[26]), "+f"(d[27]), "+f"(d[28]), "+f"(d[29]), "+f"(d[30]), "+f"(d[31]), "+f"(d[32]), "+f"(d[33]), "+f"(d[34]), "+f"(d[35]), "+f"(d[36]), "+f"(d[37]), "+f"(d[38]), "+f"(d[39]), "+f"(d[40]), "+f"(d[41]), "+f"(d[42]), "+f"(d[43]), "+f"(d[44]), "+f"(d[45]), "+f"(d[46]), "+f"(d[47]), "+f"(d[48]), "+f"(d[49]), "+f"(d[50]), "+f"(d[51]), "+f"(d[52]), "+f"(d[53]), "+f"(d[54]), "+f"(d[55]), "+f"(d[56]), "+f"(d[57]), "+f"(d[58]), "+f"(d[59]), "+f"(d[60]), "+f"(d[61]), "+f"(d[62]), "+f"(d[63]), "+f"(d[64]), "+f"(d[65]), "+f"(d[66]), "+f"(d[67]), "+f"(d[68]), "+f"(d[69]), "+f"(d[70]), "+f"(d[71]), "+f"(d[72]), "+f"(d[73]), "+f"(d[74]), "+f"(d[75]), "+f"(d[76]), "+f"(d[77]), "+f"(d[78]), "+f"(d[79]), "+f"(d[80]), "+f"(d[81]), "+f"(d[82]), "+f"(d[83]), "+f"(d[84]), "+f"(d[85]), "+f"(d[86]), "+f"(d[87]), "+f"(d[88]), "+f"(d[89]), "+f"(d[90]), "+f"(d[91]), "+f"(d[92]), "+f"(d[93]), "+f"(d[94]), "+f"(d[95])
    : "r"(a0), "r"(a1), "r"(a2), "r"(a3), "l"(descB), "r"(scaleD));
}

__device__ __forceinline__ void wgmma_m64n64k16_rs(float (&d)[32], uint32_t a0, uint32_t a1, uint32_t a2, uint32_t a3, uint64_t descB, int scaleD) {
  asm volatile("{\n.reg .pred p;\nsetp.ne.b32 p, %37, 0;\n"
    "wgmma.mma_async.sync.aligned.m64n64k16.f32.bf16.bf16 "
    "{%0, %1, %2, %3, %4, %5, %6, %7, %8, %9, %10, %11, %12, %13, %14, %15, %16, %17, %18, %19, %20, %21, %22, %23, %24, %25, %26, %27, %28, %29, %30, %31}, {%32, %33, %34, %35}, %36, p, 1, 1, 0;\n}\n"
    : "+f"(d[0]), "+f"(d[1]), "+f"(d[2]), "+f"(d[3]), "+f"(d[4]), "+f"(d[5]), "+f"(d[6]), "+f"(d[7]), "+f"(d[8]), "+f"(d[9]), "+f"(d[10]), "+f"(d[11]), "+f"(d[12]), "+f"(d[13]), "+f"(d[14]), "+f"(d[15]), "+f"(d[16]), "+f"(d[17]), "+f"(d[18]), "+f"(d[19]), "+f"(d[20]), "+f"(d[21]), "+f"(d[22]), "+f"(d[23]), "+f"(d[24]), "+f"(d[25]), "+f"(d[26]), "+f"(d[27]), "+f"(d[28]), "+f"(d[29]), "+f"(d[30]), "+f"(d[31])
    : "r"(a0), "r"(a1), "r"(a2), "r"(a3), "l"(descB), "r"(scaleD));
}

__device__ __forceinline__ void wgmma_m64n56k16_rs(float (&d)[28], uint32_t a0, uint32_t a1, uint32_t a2, uint32_t a3, uint64_t descB, int scaleD) {
  asm volatile("{\n.reg .pred p;\nsetp.ne.b32 p, %33, 0;\n"
    "wgmma.mma_async.sync.aligned.m64n56k16.f32.bf16.bf16 "
    "{%0, %1, %2, %3, %4, %5, %6, %7, %8, %9, %10, %11, %12, %13, %14, %15, %16, %17, %18, %19, %20, %21, %22, %23, %24, %25, %26, %27}, {%28, %29, %30, %31}, %32, p, 1, 1, 0;\n}\n"
    : "+f"(d[0]), "+f"(d[1]), "+f"(d[2]), "+f"(d[3]), "+f"(d[4]), "+f"(d[5]), "+f"(d[6]), "+f"(d[7]), "+f"(d[8]), "+f"(d[9]), "+f"(d[10]), "+f"(d[11]), "+f"(d[12]), "+f"(d[13]), "+f"(d[14]), "+f"(d[15]), "+f"(d[16]), "+f"(d[17]), "+f"(d[18]), "+f"(d[19]), "+f"(d[20]), "+f"(d[21]), "+f"(d[22]), "+f"(d[23]), "+f"(d[24]), "+f"(d[25]), "+f"(d[26]), "+f"(d[27])
    : "r"(a0), "r"(a1), "r"(a2), "r"(a3), "l"(descB), "r"(scaleD));
}

__global__ void __launch_bounds__(128) merge_weights_kernel(const __nv_bfloat16* __restrict__ wqkv_t,
                                                            const __nv_bfloat16* __restrict__ wo_t,
                                                            const __nv_bfloat16* __restrict__ wqkv_s,
                                                            const __nv_bfloat16* __restrict__ wo_s) {
  __shared__ __align__(16) float sA[16][196];
  __shared__ __align__(16) float sB[32][196];
  const int b = blockIdx.x;
  const int mat = b / 72;
  const int kt = (b % 72) / 6, nt = b % 6;
  const __nv_bfloat16* wqkv = (mat < 2) ? wqkv_t : wqkv_s;
  const __nv_bfloat16* wo = (mat < 2) ? wo_t : wo_s;
  const bool isU = mat & 1;
  const int tid = threadIdx.x;
  for (int i = tid; i < 16 * 96; i += 128) {
    int r = i / 96, d2 = i % 96;
    __nv_bfloat162 v = *reinterpret_cast<const __nv_bfloat162*>(wqkv + (kt * 16 + r) * 576 + (isU ? 384 : 0) + 2 * d2);
    sA[r][2 * d2] = __low2float(v);
    sA[r][2 * d2 + 1] = __high2float(v);
  }
  if (!isU) {
    for (int i = tid; i < 32 * 96; i += 128) {
      int r = i / 96, d2 = i % 96;
      __nv_bfloat162 v = *reinterpret_cast<const __nv_bfloat162*>(wqkv + (nt * 32 + r) * 576 + 192 + 2 * d2);
      sB[r][2 * d2] = __low2float(v);
      sB[r][2 * d2 + 1] = __high2float(v);
    }
  } else {
    for (int i = tid; i < 192 * 16; i += 128) {
      int d = i / 16, r2 = i % 16;
      __nv_bfloat162 v = *reinterpret_cast<const __nv_bfloat162*>(wo + d * 192 + nt * 32 + 2 * r2);
      sB[2 * r2][d] = __low2float(v);
      sB[2 * r2 + 1][d] = __high2float(v);
    }
  }
  __syncthreads();
  const int n = tid & 31, k0 = (tid >> 5) * 4;
  float acc[4] = {0.f, 0.f, 0.f, 0.f};
#pragma unroll 4
  for (int d = 0; d < 192; d += 4) {
    const float4 bv = *reinterpret_cast<const float4*>(&sB[n][d]);
#pragma unroll
    for (int j = 0; j < 4; j++) {
      const float4 av = *reinterpret_cast<const float4*>(&sA[k0 + j][d]);
      acc[j] = fmaf(av.x, bv.x, fmaf(av.y, bv.y, fmaf(av.z, bv.z, fmaf(av.w, bv.w, acc[j]))));
    }
  }
  unsigned char* img = g_wimg[mat >> 1][mat & 1];
  const int nn = nt * 32 + n;
#pragma unroll
  for (int j = 0; j < 4; j++) {
    const int k = kt * 16 + k0 + j;
    size_t off = (size_t)(k / 64) * WBLK_BYTES + (size_t)nn * 128 + (size_t)((((k % 64) / 8) ^ (nn % 8)) * 16) + (k % 8) * 2;
    *reinterpret_cast<__nv_bfloat16*>(img + off) = __float2bfloat16(acc[j]);
  }
}

template <int STAGE>
__global__ void __launch_bounds__(512, 1) stage_kernel(const __grid_constant__ CUtensorMap map_in,
                                                       __nv_bfloat16* __restrict__ out) {
  extern __shared__ unsigned char smem_raw[];
  const uint32_t sbase = (smem_u32(smem_raw) + 1023u) & ~1023u;
  const int tid = threadIdx.x;
  const int warp = tid >> 5, lane = tid & 31;
  const int NT = (STAGE == 1) ? NT1 : NT2;
  const uint32_t bar_full = sbase + SM_BAR;
  const uint32_t bar_ready = bar_full + 8 * NSLOT;
  const uint32_t bar_out = bar_ready + 8 * NSLOT;
  const uint32_t bar_free = bar_out + 8 * NSLOT;
  const uint32_t bar_w = bar_free + 8 * NSLOT;

  if (tid == 0) {
    for (int s = 0; s < NSLOT; s++) {
      mbar_init(bar_full + 8 * s, 1);
      mbar_init(bar_ready + 8 * s, 8);
      mbar_init(bar_out + 8 * s, 4);
      mbar_init(bar_free + 8 * s, 8);
    }
    mbar_init(bar_w, 1);
    asm volatile("fence.mbarrier_init.release.cluster;" ::: "memory");
  }
  if (STAGE == 2) {
    for (int i = tid; i < NSLOT * 3 * 15 * 8; i += 512) {
      int s = i / 360, r = i % 360;
      int blk = r / 120, rr = r % 120;
      uint32_t addr = sbase + SM_SLOT + s * SLOT_BYTES + blk * BLK_BYTES + (49 + rr / 8) * 128 + (rr % 8) * 16;
      sts_u4(addr, make_uint4(0, 0, 0, 0));
    }
    fence_proxy_async();
  }
  __syncthreads();

  const int ntiles = (NT - (int)blockIdx.x + (int)gridDim.x - 1) / (int)gridDim.x;

  if (warp >= 8) {
    asm volatile("setmaxnreg.dec.sync.aligned.u32 48;");
    const int pw = warp - 8;
    const int sq4 = lane & 3;

    auto issue_load = [&](int i) {
      const int slot = i % NSLOT;
      const uint32_t sl = sbase + SM_SLOT + slot * SLOT_BYTES;
      const int tile = blockIdx.x + i * gridDim.x;
      if (STAGE == 1) {
        mbar_expect_tx(bar_full + 8 * slot, 3 * BLK_BYTES);
        for (int cb = 0; cb < 3; cb++) tma_load_3d(sl + cb * BLK_BYTES, &map_in, cb * 64, 0, tile * 16, bar_full + 8 * slot);
      } else {
        const int t = tile >> 10, wh = (tile >> 5) & 31, ww = tile & 31;
        mbar_expect_tx(bar_full + 8 * slot, 3 * 49 * 128);
        for (int cb = 0; cb < 3; cb++) tma_load_4d(sl + cb * BLK_BYTES, &map_in, cb * 64, ww * 7, wh * 7, t, bar_full + 8 * slot);
      }
    };
    auto prefetch = [&](int k) {
      if (k < ntiles) {
        const int tp = blockIdx.x + k * gridDim.x;
        if (STAGE == 1) {
          for (int cb = 0; cb < 3; cb++) tma_prefetch_3d(&map_in, cb * 64, 0, tp * 16);
        } else {
          const int t = tp >> 10, wh = (tp >> 5) & 31, ww = tp & 31;
          for (int cb = 0; cb < 3; cb++) tma_prefetch_4d(&map_in, cb * 64, ww * 7, wh * 7, t);
        }
      }
    };
    auto do_stats = [&](int i) {
      const int slot = i % NSLOT;
      const uint32_t par = (i / NSLOT) & 1;
      const uint32_t sl = sbase + SM_SLOT + slot * SLOT_BYTES;
      mbar_wait(bar_full + 8 * slot, par);
      {
        const int srow = pw * 8 + (lane >> 2);
        const uint32_t rbase = sl + srow * 128;
        const uint32_t sx = (uint32_t)((srow & 7) << 4);
        float a0 = 0.f, a1 = 0.f, a2 = 0.f, a3 = 0.f, b0 = 0.f, b1 = 0.f, b2 = 0.f, b3 = 0.f;
        float pivot = 0.f;
#pragma unroll
        for (int hh = 0; hh < 2; hh++) {
          uint4 v[3];
#pragma unroll
          for (int c = 0; c < 3; c++) {
            const uint32_t chunk = sq4 * 6 + hh * 3 + c;
            v[c] = lds_u4(rbase + (chunk >> 3) * BLK_BYTES + (((chunk & 7) << 4) ^ sx));
          }
          if (hh == 0) pivot = bf_lo(__shfl_sync(0xffffffffu, v[0].x, lane & ~3));
#pragma unroll
          for (int c = 0; c < 3; c++) {
            float d0 = bf_lo(v[c].x) - pivot, d1 = bf_hi(v[c].x) - pivot, d2 = bf_lo(v[c].y) - pivot, d3 = bf_hi(v[c].y) - pivot;
            float d4 = bf_lo(v[c].z) - pivot, d5 = bf_hi(v[c].z) - pivot, d6 = bf_lo(v[c].w) - pivot, d7 = bf_hi(v[c].w) - pivot;
            a0 += d0 + d4; a1 += d1 + d5; a2 += d2 + d6; a3 += d3 + d7;
            b0 = fmaf(d0, d0, b0); b1 = fmaf(d1, d1, b1); b2 = fmaf(d2, d2, b2); b3 = fmaf(d3, d3, b3);
            b0 = fmaf(d4, d4, b0); b1 = fmaf(d5, d5, b1); b2 = fmaf(d6, d6, b2); b3 = fmaf(d7, d7, b3);
          }
        }
        float s1 = (a0 + a1) + (a2 + a3), s2 = (b0 + b1) + (b2 + b3);
        s1 += __shfl_xor_sync(0xffffffffu, s1, 1);
        s2 += __shfl_xor_sync(0xffffffffu, s2, 1);
        s1 += __shfl_xor_sync(0xffffffffu, s1, 2);
        s2 += __shfl_xor_sync(0xffffffffu, s2, 2);
        const float dm = s1 * (1.0f / 192.0f);
        const float mean = pivot + dm;
        const float var = fmaxf(fmaf(-dm, dm, s2 * (1.0f / 192.0f)), 0.f);
        const float rstd = rsqrtf(var + 1e-5f);
        if (sq4 == 0) {
          const float SC = 0.07216878364870322f * 1.4426950408889634f;
          float a = rstd * SC;
          sts_f4(sbase + SM_STATS + slot * 1024 + srow * 16, make_float4(rstd, mean, a, a * mean));
        }
      }
      __syncwarp();
      if (lane == 0) mbar_arrive(bar_ready + 8 * slot);
    };

    if (pw == 0 && lane == 0) {
      mbar_expect_tx(bar_w, 2 * WMAT_BYTES);
      const unsigned char* src = g_wimg[STAGE - 1][0];
      for (int i = 0; i < 6; i++) bulk_load(sbase + SM_WM + i * WBLK_BYTES, src + i * WBLK_BYTES, WBLK_BYTES, bar_w);
      for (int i = 0; i < NSLOT && i < ntiles; i++) issue_load(i);
      for (int k = NSLOT; k < NSLOT + 2; k++) prefetch(k);
    }
    __syncwarp();
    for (int i = 0; i < NSLOT && i < ntiles; i++) do_stats(i);

    for (int k = 0; k < ntiles; k++) {
      const int slot = k % NSLOT;
      const uint32_t sl = sbase + SM_SLOT + slot * SLOT_BYTES;
      const int tile = blockIdx.x + k * gridDim.x;
      mbar_wait(bar_out + 8 * slot, (k / NSLOT) & 1);
#pragma unroll
      for (int rg = 0; rg < 2; rg++) {
        const int row = 8 * pw + 4 * rg + (lane >> 3);
        __nv_bfloat16* orow;
        bool valid = true;
        if (STAGE == 1) {
          orow = out + ((size_t)(row & 3) * HW_DIM + (size_t)tile * 16 + (row >> 2)) * C_DIM;
        } else {
          const int t = tile >> 10, wh = (tile >> 5) & 31, ww = tile & 31;
          const int rh = row / 7;
          orow = out + ((size_t)t * HW_DIM + (size_t)(wh * 7 + rh) * 224 + ww * 7 + (row - rh * 7)) * C_DIM;
          valid = row < 49;
        }
        const uint32_t rb = sl + row * 128 + ((((lane & 7) ^ (row & 7))) << 4);
        uint4 v0 = lds_u4(rb), v1 = lds_u4(rb + BLK_BYTES), v2 = lds_u4(rb + 2 * BLK_BYTES);
        if (valid) {
          *reinterpret_cast<uint4*>(orow + (lane & 7) * 8) = v0;
          *reinterpret_cast<uint4*>(orow + 64 + (lane & 7) * 8) = v1;
          *reinterpret_cast<uint4*>(orow + 128 + (lane & 7) * 8) = v2;
        }
      }
      __syncwarp();
      if (lane == 0) mbar_arrive(bar_free + 8 * slot);
      if (k + NSLOT < ntiles) {
        if (pw == 0 && lane == 0) {
          mbar_wait(bar_free + 8 * slot, (k / NSLOT) & 1);
          issue_load(k + NSLOT);
          prefetch(k + NSLOT + 2);
        }
        __syncwarp();
        do_stats(k + NSLOT);
      }
    }
  } else {
    asm volatile("setmaxnreg.inc.sync.aligned.u32 208;");
    const int wg = warp >> 2;
    const int w = warp & 3;
    const int q = lane & 3, r = lane >> 2;
    const int row0 = 16 * w + r, row1 = row0 + 8;

    mbar_wait(bar_w, 0);
    if (tid < 192) {
      float s = 0.f;
      const uint32_t rowb = sbase + SM_WM + tid * 128;
#pragma unroll
      for (int kb = 0; kb < 3; kb++)
#pragma unroll
        for (int c = 0; c < 8; c++) {
          uint4 v = lds_u4(rowb + kb * WBLK_BYTES + ((c ^ (tid & 7)) << 4));
          s += (bf_lo(v.x) + bf_hi(v.x)) + (bf_lo(v.y) + bf_hi(v.y)) + (bf_lo(v.z) + bf_hi(v.z)) + (bf_lo(v.w) + bf_hi(v.w));
        }
      sts_f32(sbase + SM_MSUM + tid * 4, s);
    }
    named_bar_sync(3, 256);

    const uint64_t dW_M = make_desc(sbase + SM_WM, 16, 1024);
    const uint64_t dW_U = make_desc(sbase + SM_WU, 16, 1024);

    for (int i = wg; i < ntiles; i += 2) {
      const int slot = i % NSLOT;
      const uint32_t par = (i / NSLOT) & 1;
      const uint32_t sl = sbase + SM_SLOT + slot * SLOT_BYTES;
      const uint32_t st = sbase + SM_STATS + slot * 1024;
      const uint64_t dX = make_desc(sl, 16, 1024);

      float acc[96];
      uint32_t pk[48];
      TL(0);
      mbar_wait(bar_full + 8 * slot, par);
      TL(1);
      wg_fence();
#pragma unroll
      for (int kb = 0; kb < 3; kb++)
#pragma unroll
        for (int kk = 0; kk < 4; kk++)
          wgmma_m64n192k16_ss(acc, dX + ((kb * BLK_BYTES + kk * 32) >> 4), dW_M + ((kb * WBLK_BYTES + kk * 32) >> 4),
                              (kb | kk) != 0);
      wg_commit();
      TL(2);
      mbar_wait(bar_ready + 8 * slot, par);
      TL(3);
      const float4 st0 = lds_f4(st + row0 * 16), st1 = lds_f4(st + row1 * 16);
      float2 msv[24];
#pragma unroll
      for (int j = 0; j < 24; j++) msv[j] = lds_f2(sbase + SM_MSUM + (8 * j + 2 * q) * 4);
      wg_wait0();
      fence_regs(acc);
      TL(4);
      float gsum0 = 0.f, gsum1 = 0.f;
      {
        const float rs0 = st0.x, mr0 = st0.x * st0.y, rs1 = st1.x, mr1 = st1.x * st1.y;
#pragma unroll
        for (int j = 0; j < 24; j++) {
          const float2 ms = msv[j];
          float g00 = fmaf(acc[4 * j + 0], rs0, -mr0 * ms.x);
          float g01 = fmaf(acc[4 * j + 1], rs0, -mr0 * ms.y);
          float g10 = fmaf(acc[4 * j + 2], rs1, -mr1 * ms.x);
          float g11 = fmaf(acc[4 * j + 3], rs1, -mr1 * ms.y);
          uint32_t p0 = pack_bf16(g00, g01), p1 = pack_bf16(g10, g11);
          pk[2 * j] = p0;
          pk[2 * j + 1] = p1;
          gsum0 += bf_lo(p0) + bf_hi(p0);
          gsum1 += bf_lo(p1) + bf_hi(p1);
        }
      }
      TL(5);
      float sacc[32];
      wg_fence();
#pragma unroll
      for (int kb = 0; kb < 3; kb++)
#pragma unroll
        for (int kk = 0; kk < 4; kk++) {
          const int s = kb * 4 + kk;
          wgmma_m64n64k16_rs(sacc, pk[4 * s + 0], pk[4 * s + 1], pk[4 * s + 2], pk[4 * s + 3],
                             dX + ((kb * BLK_BYTES + kk * 32) >> 4), s != 0);
        }
      wg_commit();
      gsum0 += __shfl_xor_sync(0xffffffffu, gsum0, 1);
      gsum0 += __shfl_xor_sync(0xffffffffu, gsum0, 2);
      gsum1 += __shfl_xor_sync(0xffffffffu, gsum1, 1);
      gsum1 += __shfl_xor_sync(0xffffffffu, gsum1, 2);
      float4 kp[16];
#pragma unroll
      for (int jj = 0; jj < 8; jj++) {
        kp[2 * jj] = lds_f4(st + (8 * jj + 2 * q) * 16);
        kp[2 * jj + 1] = lds_f4(st + (8 * jj + 2 * q + 1) * 16);
      }
      wg_wait0();
      fence_regs(sacc);
      TL(6);
      uint32_t pf[16];
      float linv0, linv1, cc0, cc1;
      {
        float sv[32];
        float mx0 = -INFINITY, mx1 = -INFINITY;
#pragma unroll
        for (int jj = 0; jj < 8; jj++) {
          const int j0 = 8 * jj + 2 * q;
          const float4 k0 = kp[2 * jj], k1 = kp[2 * jj + 1];
          float s00 = fmaf(k0.z, sacc[4 * jj + 0], -k0.w * gsum0);
          float s01 = fmaf(k1.z, sacc[4 * jj + 1], -k1.w * gsum0);
          float s10 = fmaf(k0.z, sacc[4 * jj + 2], -k0.w * gsum1);
          float s11 = fmaf(k1.z, sacc[4 * jj + 3], -k1.w * gsum1);
          bool v00, v01, v10, v11;
          if (STAGE == 1) {
            v00 = (j0 >> 2) == (row0 >> 2);
            v01 = ((j0 + 1) >> 2) == (row0 >> 2);
            v10 = (j0 >> 2) == (row1 >> 2);
            v11 = ((j0 + 1) >> 2) == (row1 >> 2);
          } else {
            v00 = v10 = j0 < 49;
            v01 = v11 = (j0 + 1) < 49;
          }
          s00 = v00 ? s00 : -INFINITY;
          s01 = v01 ? s01 : -INFINITY;
          s10 = v10 ? s10 : -INFINITY;
          s11 = v11 ? s11 : -INFINITY;
          sv[4 * jj + 0] = s00; sv[4 * jj + 1] = s01; sv[4 * jj + 2] = s10; sv[4 * jj + 3] = s11;
          mx0 = fmaxf(mx0, fmaxf(s00, s01));
          mx1 = fmaxf(mx1, fmaxf(s10, s11));
        }
        mx0 = fmaxf(mx0, __shfl_xor_sync(0xffffffffu, mx0, 1));
        mx0 = fmaxf(mx0, __shfl_xor_sync(0xffffffffu, mx0, 2));
        mx1 = fmaxf(mx1, __shfl_xor_sync(0xffffffffu, mx1, 1));
        mx1 = fmaxf(mx1, __shfl_xor_sync(0xffffffffu, mx1, 2));
        float l0 = 0.f, l1 = 0.f;
        cc0 = 0.f; cc1 = 0.f;
#pragma unroll
        for (int jj = 0; jj < 8; jj++) {
          const int j0 = 8 * jj + 2 * q;
          const float4 k0 = kp[2 * jj], k1 = kp[2 * jj + 1];
          float p00 = ex2(sv[4 * jj + 0] - mx0), p01 = ex2(sv[4 * jj + 1] - mx0);
          float p10 = ex2(sv[4 * jj + 2] - mx1), p11 = ex2(sv[4 * jj + 3] - mx1);
          l0 += p00 + p01;
          l1 += p10 + p11;
          uint32_t f0 = pack_bf16(p00 * k0.x, p01 * k1.x);
          uint32_t f1 = pack_bf16(p10 * k0.x, p11 * k1.x);
          cc0 = fmaf(bf_lo(f0), k0.y, fmaf(bf_hi(f0), k1.y, cc0));
          cc1 = fmaf(bf_lo(f1), k0.y, fmaf(bf_hi(f1), k1.y, cc1));
          pf[2 * jj] = f0;
          pf[2 * jj + 1] = f1;
        }
        l0 += __shfl_xor_sync(0xffffffffu, l0, 1);
        l0 += __shfl_xor_sync(0xffffffffu, l0, 2);
        l1 += __shfl_xor_sync(0xffffffffu, l1, 1);
        l1 += __shfl_xor_sync(0xffffffffu, l1, 2);
        cc0 += __shfl_xor_sync(0xffffffffu, cc0, 1);
        cc0 += __shfl_xor_sync(0xffffffffu, cc0, 2);
        cc1 += __shfl_xor_sync(0xffffffffu, cc1, 1);
        cc1 += __shfl_xor_sync(0xffffffffu, cc1, 2);
        linv0 = 1.0f / l0;
        linv1 = 1.0f / l1;
      }
      TL(7);
      {
        const uint64_t dXt = make_desc(sl, BLK_BYTES, 1024);
        wg_fence();
#pragma unroll
        for (int s = 0; s < 4; s++)
          wgmma_m64n192k16_rs_tb(acc, pf[4 * s + 0], pf[4 * s + 1], pf[4 * s + 2], pf[4 * s + 3], dXt + ((s * 2048) >> 4),
                                 s != 0);
        wg_commit();
        wg_wait0();
        fence_regs(acc);
      }
      TL(8);
#pragma unroll
      for (int j = 0; j < 24; j++) {
        pk[2 * j] = pack_bf16((acc[4 * j + 0] - cc0) * linv0, (acc[4 * j + 1] - cc0) * linv0);
        pk[2 * j + 1] = pack_bf16((acc[4 * j + 2] - cc1) * linv1, (acc[4 * j + 3] - cc1) * linv1);
      }
      TL(9);
      wg_fence();
#pragma unroll
      for (int kb = 0; kb < 3; kb++)
#pragma unroll
        for (int kk = 0; kk < 4; kk++) {
          const int s = kb * 4 + kk;
          wgmma_m64n192k16_rs(acc, pk[4 * s + 0], pk[4 * s + 1], pk[4 * s + 2], pk[4 * s + 3],
                              dW_U + ((kb * WBLK_BYTES + kk * 32) >> 4), s != 0);
        }
      wg_commit();
      wg_wait0();
      fence_regs(acc);
      TL(10);
      {
        const int mrow = 16 * w + ((lane >> 3) & 1) * 8 + (lane & 7);
        const uint32_t abase = sl + mrow * 128;
#pragma unroll
        for (int j = 0; j < 24; j += 2) {
          const int chunk = j + (lane >> 4);
          const uint32_t addr = abase + (chunk >> 3) * BLK_BYTES + (((chunk & 7) ^ (lane & 7)) << 4);
          ldsm_x4(addr, pk[2 * j], pk[2 * j + 1], pk[2 * j + 2], pk[2 * j + 3]);
        }
#pragma unroll
        for (int j = 0; j < 24; j++) {
          pk[2 * j] = pack_bf16(acc[4 * j + 0] + bf_lo(pk[2 * j]), acc[4 * j + 1] + bf_hi(pk[2 * j]));
          pk[2 * j + 1] = pack_bf16(acc[4 * j + 2] + bf_lo(pk[2 * j + 1]), acc[4 * j + 3] + bf_hi(pk[2 * j + 1]));
        }
#pragma unroll
        for (int j = 0; j < 24; j += 2) {
          const int chunk = j + (lane >> 4);
          const uint32_t addr = abase + (chunk >> 3) * BLK_BYTES + (((chunk & 7) ^ (lane & 7)) << 4);
          stsm_x4(addr, pk[2 * j], pk[2 * j + 1], pk[2 * j + 2], pk[2 * j + 3]);
        }
        __syncwarp();
        if (lane == 0) mbar_arrive(bar_out + 8 * slot);
      }
      TL(11);
    }
  }
}

typedef CUresult (*PFN_encodeTiled)(CUtensorMap*, CUtensorMapDataType, cuuint32_t, void*, const cuuint64_t*, const cuuint64_t*,
                                    const cuuint32_t*, const cuuint32_t*, CUtensorMapInterleave, CUtensorMapSwizzle,
                                    CUtensorMapL2promotion, CUtensorMapFloatOOBfill);

static PFN_encodeTiled get_encode() {
  static PFN_encodeTiled fn = nullptr;
  if (!fn) {
    void* p = nullptr;
    cudaDriverEntryPointQueryResult qres;
    cudaGetDriverEntryPoint("cuTensorMapEncodeTiled", &p, cudaEnableDefault, &qres);
    fn = (PFN_encodeTiled)p;
  }
  return fn;
}

extern "C" void kernel_launch(void* const* d_in, const int* in_sizes, int n_in, void* d_out, int out_size) {
  (void)in_sizes; (void)n_in; (void)out_size;
  const __nv_bfloat16* x = (const __nv_bfloat16*)d_in[0];
  const __nv_bfloat16* wqkv_t = (const __nv_bfloat16*)d_in[1];
  const __nv_bfloat16* wo_t = (const __nv_bfloat16*)d_in[2];
  const __nv_bfloat16* wqkv_s = (const __nv_bfloat16*)d_in[3];
  const __nv_bfloat16* wo_s = (const __nv_bfloat16*)d_in[4];
  PFN_encodeTiled enc = get_encode();

  CUtensorMap m1_in, m1_out, m2;
  {
    cuuint64_t dims[3] = {192, 4, 50176};
    cuuint64_t strides[2] = {(cuuint64_t)HW_DIM * 384, 384};
    cuuint32_t box[3] = {64, 4, 16};
    cuuint32_t es[3] = {1, 1, 1};
    enc(&m1_in, CU_TENSOR_MAP_DATA_TYPE_BFLOAT16, 3, (void*)x, dims, strides, box, es, CU_TENSOR_MAP_INTERLEAVE_NONE,
        CU_TENSOR_MAP_SWIZZLE_128B, CU_TENSOR_MAP_L2_PROMOTION_L2_256B, CU_TENSOR_MAP_FLOAT_OOB_FILL_NONE);
    enc(&m1_out, CU_TENSOR_MAP_DATA_TYPE_BFLOAT16, 3, d_out, dims, strides, box, es, CU_TENSOR_MAP_INTERLEAVE_NONE,
        CU_TENSOR_MAP_SWIZZLE_128B, CU_TENSOR_MAP_L2_PROMOTION_L2_256B, CU_TENSOR_MAP_FLOAT_OOB_FILL_NONE);
  }
  {
    cuuint64_t dims[4] = {192, 224, 224, 4};
    cuuint64_t strides[3] = {384, 224 * 384, (cuuint64_t)HW_DIM * 384};
    cuuint32_t box[4] = {64, 7, 7, 1};
    cuuint32_t es[4] = {1, 1, 1, 1};
    enc(&m2, CU_TENSOR_MAP_DATA_TYPE_BFLOAT16, 4, d_out, dims, strides, box, es, CU_TENSOR_MAP_INTERLEAVE_NONE,
        CU_TENSOR_MAP_SWIZZLE_128B, CU_TENSOR_MAP_L2_PROMOTION_L2_256B, CU_TENSOR_MAP_FLOAT_OOB_FILL_NONE);
  }
  const int smem = SM_TOTAL + 1024;
  cudaFuncSetAttribute(stage_kernel<1>, cudaFuncAttributeMaxDynamicSharedMemorySize, smem);
  cudaFuncSetAttribute(stage_kernel<2>, cudaFuncAttributeMaxDynamicSharedMemorySize, smem);
  int nsm = 132;
  cudaDeviceGetAttribute(&nsm, cudaDevAttrMultiProcessorCount, 0);

  merge_weights_kernel<<<288, 128>>>(wqkv_t, wo_t, wqkv_s, wo_s);
  stage_kernel<1><<<nsm, 512, smem>>>(m1_in, (__nv_bfloat16*)d_out);
  stage_kernel<2><<<nsm, 512, smem>>>(m2, (__nv_bfloat16*)d_out);
}
```

```cpp
#include <cuda_runtime.h>
#include <cuda_bf16.h>
#include <cuda.h>
#include <stdint.h>

#define C_DIM 192
#define T_DIM 4
#define HW_DIM 50176
#define NT1 3136
#define NT2 4096

#define SLOT_BYTES 24576
#define BLK_BYTES 8192
#define WMAT_BYTES 73728
#define WBLK_BYTES 24576
#define NSLOT 3

#define SM_WM 0
#define SM_WU WMAT_BYTES
#define SM_SLOT (2 * WMAT_BYTES)
#define SM_ONES (SM_SLOT + NSLOT * SLOT_BYTES)
#define SM_STATS (SM_ONES + 1024)
#define SM_MSUM (SM_STATS + NSLOT * 1024)
#define SM_BAR (SM_MSUM + 768)
#define SM_TOTAL (SM_BAR + 256)

__device__ __align__(1024) unsigned char g_wimg[2][2][WMAT_BYTES];
#define TL(idx)
#define TLP(idx)

__device__ __forceinline__ uint32_t smem_u32(const void* p) { return (uint32_t)__cvta_generic_to_shared(p); }

__device__ __forceinline__ void mbar_init(uint32_t bar, uint32_t count) {
  asm volatile("mbarrier.init.shared::cta.b64 [%0], %1;" ::"r"(bar), "r"(count) : "memory");
}
__device__ __forceinline__ void mbar_expect_tx(uint32_t bar, uint32_t bytes) {
  asm volatile("mbarrier.arrive.expect_tx.shared::cta.b64 _, [%0], %1;" ::"r"(bar), "r"(bytes) : "memory");
}
__device__ __forceinline__ void mbar_arrive(uint32_t bar) {
  asm volatile("mbarrier.arrive.shared::cta.b64 _, [%0];" ::"r"(bar) : "memory");
}
__device__ __forceinline__ bool mbar_try_wait(uint32_t bar, uint32_t parity) {
  uint32_t ok;
  asm volatile(
      "{\n.reg .pred p;\nmbarrier.try_wait.parity.shared::cta.b64 p, [%1], %2;\nselp.u32 %0, 1, 0, p;\n}\n"
      : "=r"(ok)
      : "r"(bar), "r"(parity)
      : "memory");
  return ok != 0;
}
__device__ __forceinline__ void mbar_wait(uint32_t bar, uint32_t parity) {
  for (uint32_t it = 0; it < (1u << 24); ++it)
    if (mbar_try_wait(bar, parity)) break;
}
__device__ __forceinline__ void fence_proxy_async() { asm volatile("fence.proxy.async.shared::cta;" ::: "memory"); }
__device__ __forceinline__ void named_bar_sync(int id, int nthreads) {
  asm volatile("bar.sync %0, %1;" ::"r"(id), "r"(nthreads) : "memory");
}

__device__ __forceinline__ void tma_load_3d(uint32_t dst, const CUtensorMap* map, int c0, int c1, int c2, uint32_t bar) {
  asm volatile(
      "cp.async.bulk.tensor.3d.shared::cluster.global.mbarrier::complete_tx::bytes [%0], [%1, {%3, %4, %5}], [%2];"
      ::"r"(dst), "l"(map), "r"(bar), "r"(c0), "r"(c1), "r"(c2) : "memory");
}
__device__ __forceinline__ void tma_load_4d(uint32_t dst, const CUtensorMap* map, int c0, int c1, int c2, int c3, uint32_t bar) {
  asm volatile(
      "cp.async.bulk.tensor.4d.shared::cluster.global.mbarrier::complete_tx::bytes [%0], [%1, {%3, %4, %5, %6}], [%2];"
      ::"r"(dst), "l"(map), "r"(bar), "r"(c0), "r"(c1), "r"(c2), "r"(c3) : "memory");
}
__device__ __forceinline__ void tma_store_3d(const CUtensorMap* map, uint32_t src, int c0, int c1, int c2) {
  asm volatile("cp.async.bulk.tensor.3d.global.shared::cta.bulk_group [%0, {%2, %3, %4}], [%1];"
               ::"l"(map), "r"(src), "r"(c0), "r"(c1), "r"(c2) : "memory");
}
__device__ __forceinline__ void tma_store_4d(const CUtensorMap* map, uint32_t src, int c0, int c1, int c2, int c3) {
  asm volatile("cp.async.bulk.tensor.4d.global.shared::cta.bulk_group [%0, {%2, %3, %4, %5}], [%1];"
               ::"l"(map), "r"(src), "r"(c0), "r"(c1), "r"(c2), "r"(c3) : "memory");
}
__device__ __forceinline__ void tma_prefetch_3d(const CUtensorMap* map, int c0, int c1, int c2) {
  asm volatile("cp.async.bulk.prefetch.tensor.3d.L2.global.tile [%0, {%1, %2, %3}];" ::"l"(map), "r"(c0), "r"(c1), "r"(c2) : "memory");
}
__device__ __forceinline__ void tma_prefetch_4d(const CUtensorMap* map, int c0, int c1, int c2, int c3) {
  asm volatile("cp.async.bulk.prefetch.tensor.4d.L2.global.tile [%0, {%1, %2, %3, %4}];" ::"l"(map), "r"(c0), "r"(c1), "r"(c2), "r"(c3) : "memory");
}
__device__ __forceinline__ void bulk_commit() { asm volatile("cp.async.bulk.commit_group;" ::: "memory"); }
__device__ __forceinline__ void bulk_wait_read0() { asm volatile("cp.async.bulk.wait_group.read 0;" ::: "memory"); }
__device__ __forceinline__ void bulk_wait0() { asm volatile("cp.async.bulk.wait_group 0;" ::: "memory"); }
__device__ __forceinline__ void bulk_load(uint32_t dst, const void* src, uint32_t bytes, uint32_t bar) {
  asm volatile("cp.async.bulk.shared::cluster.global.mbarrier::complete_tx::bytes [%0], [%1], %2, [%3];"
               ::"r"(dst), "l"(src), "r"(bytes), "r"(bar) : "memory");
}

__device__ __forceinline__ void wg_fence() { asm volatile("wgmma.fence.sync.aligned;" ::: "memory"); }
__device__ __forceinline__ void wg_commit() { asm volatile("wgmma.commit_group.sync.aligned;" ::: "memory"); }
__device__ __forceinline__ void wg_wait0() { asm volatile("wgmma.wait_group.sync.aligned 0;" ::: "memory"); }
template <int N>
__device__ __forceinline__ void fence_regs(float (&d)[N]) {
#pragma unroll
  for (int i = 0; i < N; i++) asm volatile("" : "+f"(d[i])::"memory");
}

__device__ __forceinline__ uint64_t make_desc(uint32_t addr, uint32_t lbo, uint32_t sbo) {
  return (uint64_t)((addr & 0x3FFFF) >> 4) | ((uint64_t)(lbo >> 4) << 16) | ((uint64_t)(sbo >> 4) << 32) | (1ull << 62);
}

__device__ __forceinline__ uint32_t pack_bf16(float lo, float hi) {
  uint32_t r;
  asm("cvt.rn.bf16x2.f32 %0, %1, %2;" : "=r"(r) : "f"(hi), "f"(lo));
  return r;
}
__device__ __forceinline__ uint32_t hadd2_bf16(uint32_t a, uint32_t b) {
  uint32_t r;
  asm("add.rn.bf16x2 %0, %1, %2;" : "=r"(r) : "r"(a), "r"(b));
  return r;
}
__device__ __forceinline__ bool __syncthreads_and_wg(bool pred, int id) {
  uint32_t res;
  asm volatile("{\n.reg .pred p, q;\nsetp.ne.u32 p, %1, 0;\nbar.red.and.pred q, %2, 128, p;\nselp.u32 %0, 1, 0, q;\n}\n"
               : "=r"(res) : "r"((uint32_t)pred), "r"(id) : "memory");
  return res != 0;
}
__device__ __forceinline__ float bf_lo(uint32_t v) { return __uint_as_float(v << 16); }
__device__ __forceinline__ float bf_hi(uint32_t v) { return __uint_as_float(v & 0xffff0000u); }

__device__ __forceinline__ void ldsm_x4(uint32_t addr, uint32_t& r0, uint32_t& r1, uint32_t& r2, uint32_t& r3) {
  asm volatile("ldmatrix.sync.aligned.m8n8.x4.shared.b16 {%0, %1, %2, %3}, [%4];"
               : "=r"(r0), "=r"(r1), "=r"(r2), "=r"(r3) : "r"(addr) : "memory");
}
__device__ __forceinline__ void stsm_x4(uint32_t addr, uint32_t r0, uint32_t r1, uint32_t r2, uint32_t r3) {
  asm volatile("stmatrix.sync.aligned.m8n8.x4.shared.b16 [%0], {%1, %2, %3, %4};"
               ::"r"(addr), "r"(r0), "r"(r1), "r"(r2), "r"(r3) : "memory");
}
__device__ __forceinline__ float4 lds_f4(uint32_t addr) {
  float4 v;
  asm volatile("ld.shared.v4.f32 {%0, %1, %2, %3}, [%4];" : "=f"(v.x), "=f"(v.y), "=f"(v.z), "=f"(v.w) : "r"(addr));
  return v;
}
__device__ __forceinline__ float2 lds_f2(uint32_t addr) {
  float2 v;
  asm volatile("ld.shared.v2.f32 {%0, %1}, [%2];" : "=f"(v.x), "=f"(v.y) : "r"(addr));
  return v;
}
__device__ __forceinline__ uint4 lds_u4(uint32_t addr) {
  uint4 v;
  asm volatile("ld.shared.v4.u32 {%0, %1, %2, %3}, [%4];" : "=r"(v.x), "=r"(v.y), "=r"(v.z), "=r"(v.w) : "r"(addr));
  return v;
}
__device__ __forceinline__ void sts_f4(uint32_t addr, float4 v) {
  asm volatile("st.shared.v4.f32 [%0], {%1, %2, %3, %4};" ::"r"(addr), "f"(v.x), "f"(v.y), "f"(v.z), "f"(v.w) : "memory");
}
__device__ __forceinline__ void sts_u4(uint32_t addr, uint4 v) {
  asm volatile("st.shared.v4.u32 [%0], {%1, %2, %3, %4};" ::"r"(addr), "r"(v.x), "r"(v.y), "r"(v.z), "r"(v.w) : "memory");
}
__device__ __forceinline__ void sts_f32(uint32_t addr, float v) {
  asm volatile("st.shared.f32 [%0], %1;" ::"r"(addr), "f"(v) : "memory");
}
__device__ __forceinline__ float ex2(float x) {
  float y;
  asm("ex2.approx.ftz.f32 %0, %1;" : "=f"(y) : "f"(x));
  return y;
}

__device__ __forceinline__ void wgmma_m64n192k16_ss(float (&d)[96], uint64_t descA, uint64_t descB, int scaleD) {
  asm volatile("{\n.reg .pred p;\nsetp.ne.b32 p, %98, 0;\n"
    "wgmma.mma_async.sync.aligned.m64n192k16.f32.bf16.bf16 "
    "{%0, %1, %2, %3, %4, %5, %6, %7, %8, %9, %10, %11, %12, %13, %14, %15, %16, %17, %18, %19, %20, %21, %22, %23, %24, %25, %26, %27, %28, %29, %30, %31, %32, %33, %34, %35, %36, %37, %38, %39, %40, %41, %42, %43, %44, %45, %46, %47, %48, %49, %50, %51, %52, %53, %54, %55, %56, %57, %58, %59, %60, %61, %62, %63, %64, %65, %66, %67, %68, %69, %70, %71, %72, %73, %74, %75, %76, %77, %78, %79, %80, %81, %82, %83, %84, %85, %86, %87, %88, %89, %90, %91, %92, %93, %94, %95}, %96, %97, p, 1, 1, 0, 0;\n}\n"
    : "+f"(d[0]), "+f"(d[1]), "+f"(d[2]), "+f"(d[3]), "+f"(d[4]), "+f"(d[5]), "+f"(d[6]), "+f"(d[7]), "+f"(d[8]), "+f"(d[9]), "+f"(d[10]), "+f"(d[11]), "+f"(d[12]), "+f"(d[13]), "+f"(d[14]), "+f"(d[15]), "+f"(d[16]), "+f"(d[17]), "+f"(d[18]), "+f"(d[19]), "+f"(d[20]), "+f"(d[21]), "+f"(d[22]), "+f"(d[23]), "+f"(d[24]), "+f"(d[25]), "+f"(d[26]), "+f"(d[27]), "+f"(d[28]), "+f"(d[29]), "+f"(d[30]), "+f"(d[31]), "+f"(d[32]), "+f"(d[33]), "+f"(d[34]), "+f"(d[35]), "+f"(d[36]), "+f"(d[37]), "+f"(d[38]), "+f"(d[39]), "+f"(d[40]), "+f"(d[41]), "+f"(d[42]), "+f"(d[43]), "+f"(d[44]), "+f"(d[45]), "+f"(d[46]), "+f"(d[47]), "+f"(d[48]), "+f"(d[49]), "+f"(d[50]), "+f"(d[51]), "+f"(d[52]), "+f"(d[53]), "+f"(d[54]), "+f"(d[55]), "+f"(d[56]), "+f"(d[57]), "+f"(d[58]), "+f"(d[59]), "+f"(d[60]), "+f"(d[61]), "+f"(d[62]), "+f"(d[63]), "+f"(d[64]), "+f"(d[65]), "+f"(d[66]), "+f"(d[67]), "+f"(d[68]), "+f"(d[69]), "+f"(d[70]), "+f"(d[71]), "+f"(d[72]), "+f"(d[73]), "+f"(d[74]), "+f"(d[75]), "+f"(d[76]), "+f"(d[77]), "+f"(d[78]), "+f"(d[79]), "+f"(d[80]), "+f"(d[81]), "+f"(d[82]), "+f"(d[83]), "+f"(d[84]), "+f"(d[85]), "+f"(d[86]), "+f"(d[87]), "+f"(d[88]), "+f"(d[89]), "+f"(d[90]), "+f"(d[91]), "+f"(d[92]), "+f"(d[93]), "+f"(d[94]), "+f"(d[95])
    : "l"(descA), "l"(descB), "r"(scaleD));
}

__device__ __forceinline__ void wgmma_m64n192k16_rs(float (&d)[96], uint32_t a0, uint32_t a1, uint32_t a2, uint32_t a3, uint64_t descB, int scaleD) {
  asm volatile("{\n.reg .pred p;\nsetp.ne.b32 p, %101, 0;\n"
    "wgmma.mma_async.sync.aligned.m64n192k16.f32.bf16.bf16 "
    "{%0, %1, %2, %3, %4, %5, %6, %7, %8, %9, %10, %11, %12, %13, %14, %15, %16, %17, %18, %19, %20, %21, %22, %23, %24, %25, %26, %27, %28, %29, %30, %31, %32, %33, %34, %35, %36, %37, %38, %39, %40, %41, %42, %43, %44, %45, %46, %47, %48, %49, %50, %51, %52, %53, %54, %55, %56, %57, %58, %59, %60, %61, %62, %63, %64, %65, %66, %67, %68, %69, %70, %71, %72, %73, %74, %75, %76, %77, %78, %79, %80, %81, %82, %83, %84, %85, %86, %87, %88, %89, %90, %91, %92, %93, %94, %95}, {%96, %97, %98, %99}, %100, p, 1, 1, 0;\n}\n"
    : "+f"(d[0]), "+f"(d[1]), "+f"(d[2]), "+f"(d[3]), "+f"(d[4]), "+f"(d[5]), "+f"(d[6]), "+f"(d[7]), "+f"(d[8]), "+f"(d[9]), "+f"(d[10]), "+f"(d[11]), "+f"(d[12]), "+f"(d[13]), "+f"(d[14]), "+f"(d[15]), "+f"(d[16]), "+f"(d[17]), "+f"(d[18]), "+f"(d[19]), "+f"(d[20]), "+f"(d[21]), "+f"(d[22]), "+f"(d[23]), "+f"(d[24]), "+f"(d[25]), "+f"(d[26]), "+f"(d[27]), "+f"(d[28]), "+f"(d[29]), "+f"(d[30]), "+f"(d[31]), "+f"(d[32]), "+f"(d[33]), "+f"(d[34]), "+f"(d[35]), "+f"(d[36]), "+f"(d[37]), "+f"(d[38]), "+f"(d[39]), "+f"(d[40]), "+f"(d[41]), "+f"(d[42]), "+f"(d[43]), "+f"(d[44]), "+f"(d[45]), "+f"(d[46]), "+f"(d[47]), "+f"(d[48]), "+f"(d[49]), "+f"(d[50]), "+f"(d[51]), "+f"(d[52]), "+f"(d[53]), "+f"(d[54]), "+f"(d[55]), "+f"(d[56]), "+f"(d[57]), "+f"(d[58]), "+f"(d[59]), "+f"(d[60]), "+f"(d[61]), "+f"(d[62]), "+f"(d[63]), "+f"(d[64]), "+f"(d[65]), "+f"(d[66]), "+f"(d[67]), "+f"(d[68]), "+f"(d[69]), "+f"(d[70]), "+f"(d[71]), "+f"(d[72]), "+f"(d[73]), "+f"(d[74]), "+f"(d[75]), "+f"(d[76]), "+f"(d[77]), "+f"(d[78]), "+f"(d[79]), "+f"(d[80]), "+f"(d[81]), "+f"(d[82]), "+f"(d[83]), "+f"(d[84]), "+f"(d[85]), "+f"(d[86]), "+f"(d[87]), "+f"(d[88]), "+f"(d[89]), "+f"(d[90]), "+f"(d[91]), "+f"(d[92]), "+f"(d[93]), "+f"(d[94]), "+f"(d[95])
    : "r"(a0), "r"(a1), "r"(a2), "r"(a3), "l"(descB), "r"(scaleD));
}

__device__ __forceinline__ void wgmma_m64n192k16_rs_tb(float (&d)[96], uint32_t a0, uint32_t a1, uint32_t a2, uint32_t a3, uint64_t descB, int scaleD) {
  asm volatile("{\n.reg .pred p;\nsetp.ne.b32 p, %101, 0;\n"
    "wgmma.mma_async.sync.aligned.m64n192k16.f32.bf16.bf16 "
    "{%0, %1, %2, %3, %4, %5, %6, %7, %8, %9, %10, %11, %12, %13, %14, %15, %16, %17, %18, %19, %20, %21, %22, %23, %24, %25, %26, %27, %28, %29, %30, %31, %32, %33, %34, %35, %36, %37, %38, %39, %40, %41, %42, %43, %44, %45, %46, %47, %48, %49, %50, %51, %52, %53, %54, %55, %56, %57, %58, %59, %60, %61, %62, %63, %64, %65, %66, %67, %68, %69, %70, %71, %72, %73, %74, %75, %76, %77, %78, %79, %80, %81, %82, %83, %84, %85, %86, %87, %88, %89, %90, %91, %92, %93, %94, %95}, {%96, %97, %98, %99}, %100, p, 1, 1, 1;\n}\n"
    : "+f"(d[0]), "+f"(d[1]), "+f"(d[2]), "+f"(d[3]), "+f"(d[4]), "+f"(d[5]), "+f"(d[6]), "+f"(d[7]), "+f"(d[8]), "+f"(d[9]), "+f"(d[10]), "+f"(d[11]), "+f"(d[12]), "+f"(d[13]), "+f"(d[14]), "+f"(d[15]), "+f"(d[16]), "+f"(d[17]), "+f"(d[18]), "+f"(d[19]), "+f"(d[20]), "+f"(d[21]), "+f"(d[22]), "+f"(d[23]), "+f"(d[24]), "+f"(d[25]), "+f"(d[26]), "+f"(d[27]), "+f"(d[28]), "+f"(d[29]), "+f"(d[30]), "+f"(d[31]), "+f"(d[32]), "+f"(d[33]), "+f"(d[34]), "+f"(d[35]), "+f"(d[36]), "+f"(d[37]), "+f"(d[38]), "+f"(d[39]), "+f"(d[40]), "+f"(d[41]), "+f"(d[42]), "+f"(d[43]), "+f"(d[44]), "+f"(d[45]), "+f"(d[46]), "+f"(d[47]), "+f"(d[48]), "+f"(d[49]), "+f"(d[50]), "+f"(d[51]), "+f"(d[52]), "+f"(d[53]), "+f"(d[54]), "+f"(d[55]), "+f"(d[56]), "+f"(d[57]), "+f"(d[58]), "+f"(d[59]), "+f"(d[60]), "+f"(d[61]), "+f"(d[62]), "+f"(d[63]), "+f"(d[64]), "+f"(d[65]), "+f"(d[66]), "+f"(d[67]), "+f"(d[68]), "+f"(d[69]), "+f"(d[70]), "+f"(d[71]), "+f"(d[72]), "+f"(d[73]), "+f"(d[74]), "+f"(d[75]), "+f"(d[76]), "+f"(d[77]), "+f"(d[78]), "+f"(d[79]), "+f"(d[80]), "+f"(d[81]), "+f"(d[82]), "+f"(d[83]), "+f"(d[84]), "+f"(d[85]), "+f"(d[86]), "+f"(d[87]), "+f"(d[88]), "+f"(d[89]), "+f"(d[90]), "+f"(d[91]), "+f"(d[92]), "+f"(d[93]), "+f"(d[94]), "+f"(d[95])
    : "r"(a0), "r"(a1), "r"(a2), "r"(a3), "l"(descB), "r"(scaleD));
}

__device__ __forceinline__ void wgmma_m64n64k16_rs(float (&d)[32], uint32_t a0, uint32_t a1, uint32_t a2, uint32_t a3, uint64_t descB, int scaleD) {
  asm volatile("{\n.reg .pred p;\nsetp.ne.b32 p, %37, 0;\n"
    "wgmma.mma_async.sync.aligned.m64n64k16.f32.bf16.bf16 "
    "{%0, %1, %2, %3, %4, %5, %6, %7, %8, %9, %10, %11, %12, %13, %14, %15, %16, %17, %18, %19, %20, %21, %22, %23, %24, %25, %26, %27, %28, %29, %30, %31}, {%32, %33, %34, %35}, %36, p, 1, 1, 0;\n}\n"
    : "+f"(d[0]), "+f"(d[1]), "+f"(d[2]), "+f"(d[3]), "+f"(d[4]), "+f"(d[5]), "+f"(d[6]), "+f"(d[7]), "+f"(d[8]), "+f"(d[9]), "+f"(d[10]), "+f"(d[11]), "+f"(d[12]), "+f"(d[13]), "+f"(d[14]), "+f"(d[15]), "+f"(d[16]), "+f"(d[17]), "+f"(d[18]), "+f"(d[19]), "+f"(d[20]), "+f"(d[21]), "+f"(d[22]), "+f"(d[23]), "+f"(d[24]), "+f"(d[25]), "+f"(d[26]), "+f"(d[27]), "+f"(d[28]), "+f"(d[29]), "+f"(d[30]), "+f"(d[31])
    : "r"(a0), "r"(a1), "r"(a2), "r"(a3), "l"(descB), "r"(scaleD));
}

__device__ __forceinline__ void wgmma_m64n56k16_rs(float (&d)[28], uint32_t a0, uint32_t a1, uint32_t a2, uint32_t a3, uint64_t descB, int scaleD) {
  asm volatile("{\n.reg .pred p;\nsetp.ne.b32 p, %33, 0;\n"
    "wgmma.mma_async.sync.aligned.m64n56k16.f32.bf16.bf16 "
    "{%0, %1, %2, %3, %4, %5, %6, %7, %8, %9, %10, %11, %12, %13, %14, %15, %16, %17, %18, %19, %20, %21, %22, %23, %24, %25, %26, %27}, {%28, %29, %30, %31}, %32, p, 1, 1, 0;\n}\n"
    : "+f"(d[0]), "+f"(d[1]), "+f"(d[2]), "+f"(d[3]), "+f"(d[4]), "+f"(d[5]), "+f"(d[6]), "+f"(d[7]), "+f"(d[8]), "+f"(d[9]), "+f"(d[10]), "+f"(d[11]), "+f"(d[12]), "+f"(d[13]), "+f"(d[14]), "+f"(d[15]), "+f"(d[16]), "+f"(d[17]), "+f"(d[18]), "+f"(d[19]), "+f"(d[20]), "+f"(d[21]), "+f"(d[22]), "+f"(d[23]), "+f"(d[24]), "+f"(d[25]), "+f"(d[26]), "+f"(d[27])
    : "r"(a0), "r"(a1), "r"(a2), "r"(a3), "l"(descB), "r"(scaleD));
}

__device__ __forceinline__ void wgmma_m64n8k16_rs(float (&d)[4], uint32_t a0, uint32_t a1, uint32_t a2, uint32_t a3, uint64_t descB, int scaleD) {
  asm volatile("{\n.reg .pred p;\nsetp.ne.b32 p, %9, 0;\n"
    "wgmma.mma_async.sync.aligned.m64n8k16.f32.bf16.bf16 "
    "{%0, %1, %2, %3}, {%4, %5, %6, %7}, %8, p, 1, 1, 0;\n}\n"
    : "+f"(d[0]), "+f"(d[1]), "+f"(d[2]), "+f"(d[3])
    : "r"(a0), "r"(a1), "r"(a2), "r"(a3), "l"(descB), "r"(scaleD));
}

__global__ void __launch_bounds__(128) merge_weights_kernel(const __nv_bfloat16* __restrict__ wqkv_t,
                                                            const __nv_bfloat16* __restrict__ wo_t,
                                                            const __nv_bfloat16* __restrict__ wqkv_s,
                                                            const __nv_bfloat16* __restrict__ wo_s) {
  asm volatile("griddepcontrol.launch_dependents;" ::: "memory");
  const int gw = blockIdx.x * 4 + (threadIdx.x >> 5);
  const int lane = threadIdx.x & 31, g = lane >> 2, q = lane & 3;
  const int mat = gw / 288;
  const int kt = (gw % 288) / 24, nt = gw % 24;
  const __nv_bfloat16* wqkv = (mat < 2) ? wqkv_t : wqkv_s;
  const __nv_bfloat16* wo = (mat < 2) ? wo_t : wo_s;
  const bool isU = mat & 1;
  uint32_t af[12][4], bf[12][2];
  const __nv_bfloat16* arow0 = wqkv + (kt * 16 + g) * 576 + (isU ? 384 : 0) + 2 * q;
  const __nv_bfloat16* arow1 = arow0 + 8 * 576;
#pragma unroll
  for (int s = 0; s < 12; s++) {
    af[s][0] = *reinterpret_cast<const uint32_t*>(arow0 + 16 * s);
    af[s][1] = *reinterpret_cast<const uint32_t*>(arow1 + 16 * s);
    af[s][2] = *reinterpret_cast<const uint32_t*>(arow0 + 16 * s + 8);
    af[s][3] = *reinterpret_cast<const uint32_t*>(arow1 + 16 * s + 8);
  }
  if (!isU) {
    const __nv_bfloat16* brow = wqkv + (nt * 8 + g) * 576 + 192 + 2 * q;
#pragma unroll
    for (int s = 0; s < 12; s++) {
      bf[s][0] = *reinterpret_cast<const uint32_t*>(brow + 16 * s);
      bf[s][1] = *reinterpret_cast<const uint32_t*>(brow + 16 * s + 8);
    }
  } else {
    const unsigned short* bcol = reinterpret_cast<const unsigned short*>(wo) + (2 * q) * 192 + nt * 8 + g;
#pragma unroll
    for (int s = 0; s < 12; s++) {
      bf[s][0] = (uint32_t)bcol[(16 * s) * 192] | ((uint32_t)bcol[(16 * s + 1) * 192] << 16);
      bf[s][1] = (uint32_t)bcol[(16 * s + 8) * 192] | ((uint32_t)bcol[(16 * s + 9) * 192] << 16);
    }
  }
  float c[4] = {0.f, 0.f, 0.f, 0.f};
#pragma unroll
  for (int s = 0; s < 12; s++)
    asm volatile("mma.sync.aligned.m16n8k16.row.col.f32.bf16.bf16.f32 {%0,%1,%2,%3}, {%4,%5,%6,%7}, {%8,%9}, {%0,%1,%2,%3};"
                 : "+f"(c[0]), "+f"(c[1]), "+f"(c[2]), "+f"(c[3])
                 : "r"(af[s][0]), "r"(af[s][1]), "r"(af[s][2]), "r"(af[s][3]), "r"(bf[s][0]), "r"(bf[s][1]));
  unsigned char* img = g_wimg[mat >> 1][mat & 1];
#pragma unroll
  for (int j = 0; j < 4; j++) {
    const int k = kt * 16 + g + (j >> 1) * 8, nn = nt * 8 + 2 * q + (j & 1);
    size_t off = (size_t)(k / 64) * WBLK_BYTES + (size_t)nn * 128 + (size_t)((((k % 64) / 8) ^ (nn % 8)) * 16) + (k % 8) * 2;
    *reinterpret_cast<__nv_bfloat16*>(img + off) = __float2bfloat16(c[j]);
  }
}

template <int STAGE>
__global__ void __launch_bounds__(512, 1) stage_kernel(const __grid_constant__ CUtensorMap map_in,
                                                       __nv_bfloat16* __restrict__ out) {
  extern __shared__ unsigned char smem_raw[];
  const uint32_t sbase = (smem_u32(smem_raw) + 1023u) & ~1023u;
  const int tid = threadIdx.x;
  const int warp = tid >> 5, lane = tid & 31;
  const int NT = (STAGE == 1) ? NT1 : NT2;
  const uint32_t bar_full = sbase + SM_BAR;
  const uint32_t bar_ready = bar_full + 8 * NSLOT;
  const uint32_t bar_out = bar_ready + 8 * NSLOT;
  const uint32_t bar_free = bar_out + 8 * NSLOT;
  const uint32_t bar_w = bar_free + 8 * NSLOT;

  if (tid == 0) {
    for (int s = 0; s < NSLOT; s++) {
      mbar_init(bar_full + 8 * s, 1);
      mbar_init(bar_ready + 8 * s, 8);
      mbar_init(bar_out + 8 * s, 4);
      mbar_init(bar_free + 8 * s, 8);
    }
    mbar_init(bar_w, 1);
    asm volatile("fence.mbarrier_init.release.cluster;" ::: "memory");
  }
  if (STAGE == 2) {
    for (int i = tid; i < NSLOT * 3 * 15 * 8; i += 512) {
      int s = i / 360, r = i % 360;
      int blk = r / 120, rr = r % 120;
      uint32_t addr = sbase + SM_SLOT + s * SLOT_BYTES + blk * BLK_BYTES + (49 + rr / 8) * 128 + (rr % 8) * 16;
      const uint32_t v = (rr < 8) ? 0x3f803f80u : 0u;
      sts_u4(addr, make_uint4(v, v, v, v));
    }
  } else {
    if (tid < 64) sts_u4(sbase + SM_ONES + tid * 16, make_uint4(0x3f803f80u, 0x3f803f80u, 0x3f803f80u, 0x3f803f80u));
  }
  fence_proxy_async();
  __syncthreads();

  const int ntiles = (NT - (int)blockIdx.x + (int)gridDim.x - 1) / (int)gridDim.x;

  if (warp >= 8) {
    asm volatile("setmaxnreg.dec.sync.aligned.u32 48;");
    const int pw = warp - 8;
    const int sq4 = lane & 3;

    auto issue_load = [&](int i) {
      const int slot = i % NSLOT;
      const uint32_t sl = sbase + SM_SLOT + slot * SLOT_BYTES;
      const int tile = blockIdx.x + i * gridDim.x;
      if (STAGE == 1) {
        mbar_expect_tx(bar_full + 8 * slot, 3 * BLK_BYTES);
        for (int cb = 0; cb < 3; cb++) tma_load_3d(sl + cb * BLK_BYTES, &map_in, cb * 64, 0, tile * 16, bar_full + 8 * slot);
      } else {
        const int t = tile >> 10, wh = (tile >> 5) & 31, ww = tile & 31;
        mbar_expect_tx(bar_full + 8 * slot, 3 * 49 * 128);
        for (int cb = 0; cb < 3; cb++) tma_load_4d(sl + cb * BLK_BYTES, &map_in, cb * 64, ww * 7, wh * 7, t, bar_full + 8 * slot);
      }
    };
    auto prefetch = [&](int k) {
      if (k < ntiles) {
        const int tp = blockIdx.x + k * gridDim.x;
        if (STAGE == 1) {
          for (int cb = 0; cb < 3; cb++) tma_prefetch_3d(&map_in, cb * 64, 0, tp * 16);
        } else {
          const int t = tp >> 10, wh = (tp >> 5) & 31, ww = tp & 31;
          for (int cb = 0; cb < 3; cb++) tma_prefetch_4d(&map_in, cb * 64, ww * 7, wh * 7, t);
        }
      }
    };
    auto do_stats = [&](int i) {
      const int slot = i % NSLOT;
      const uint32_t par = (i / NSLOT) & 1;
      const uint32_t sl = sbase + SM_SLOT + slot * SLOT_BYTES;
      mbar_wait(bar_full + 8 * slot, par);
      {
        const int srow = pw * 8 + (lane >> 2);
        const uint32_t rbase = sl + srow * 128;
        const uint32_t sx = (uint32_t)((srow & 7) << 4);
        float a0 = 0.f, a1 = 0.f, a2 = 0.f, a3 = 0.f, b0 = 0.f, b1 = 0.f, b2 = 0.f, b3 = 0.f;
        float pivot = 0.f;
#pragma unroll
        for (int hh = 0; hh < 2; hh++) {
          uint4 v[3];
#pragma unroll
          for (int c = 0; c < 3; c++) {
            const uint32_t chunk = sq4 * 6 + hh * 3 + c;
            v[c] = lds_u4(rbase + (chunk >> 3) * BLK_BYTES + (((chunk & 7) << 4) ^ sx));
          }
          if (hh == 0) pivot = bf_lo(__shfl_sync(0xffffffffu, v[0].x, lane & ~3));
#pragma unroll
          for (int c = 0; c < 3; c++) {
            float d0 = bf_lo(v[c].x) - pivot, d1 = bf_hi(v[c].x) - pivot, d2 = bf_lo(v[c].y) - pivot, d3 = bf_hi(v[c].y) - pivot;
            float d4 = bf_lo(v[c].z) - pivot, d5 = bf_hi(v[c].z) - pivot, d6 = bf_lo(v[c].w) - pivot, d7 = bf_hi(v[c].w) - pivot;
            a0 += d0 + d4; a1 += d1 + d5; a2 += d2 + d6; a3 += d3 + d7;
            b0 = fmaf(d0, d0, b0); b1 = fmaf(d1, d1, b1); b2 = fmaf(d2, d2, b2); b3 = fmaf(d3, d3, b3);
            b0 = fmaf(d4, d4, b0); b1 = fmaf(d5, d5, b1); b2 = fmaf(d6, d6, b2); b3 = fmaf(d7, d7, b3);
          }
        }
        float s1 = (a0 + a1) + (a2 + a3), s2 = (b0 + b1) + (b2 + b3);
        s1 += __shfl_xor_sync(0xffffffffu, s1, 1);
        s2 += __shfl_xor_sync(0xffffffffu, s2, 1);
        s1 += __shfl_xor_sync(0xffffffffu, s1, 2);
        s2 += __shfl_xor_sync(0xffffffffu, s2, 2);
        const float dm = s1 * (1.0f / 192.0f);
        const float mean = pivot + dm;
        const float var = fmaxf(fmaf(-dm, dm, s2 * (1.0f / 192.0f)), 0.f);
        const float rstd = rsqrtf(var + 1e-5f);
        if (sq4 == 0) {
          const float SC = 0.07216878364870322f * 1.4426950408889634f;
          float a = rstd * SC;
          sts_f4(sbase + SM_STATS + slot * 1024 + srow * 16, make_float4(rstd, mean, a, rstd * mean));
        }
      }
      __syncwarp();
      if (lane == 0) mbar_arrive(bar_ready + 8 * slot);
    };

    if (pw == 0 && lane == 0) {
      asm volatile("griddepcontrol.launch_dependents;" ::: "memory");
      asm volatile("griddepcontrol.wait;" ::: "memory");
      mbar_expect_tx(bar_w, 2 * WMAT_BYTES);
      const unsigned char* src = g_wimg[STAGE - 1][0];
      for (int i = 0; i < 6; i++) bulk_load(sbase + SM_WM + i * WBLK_BYTES, src + i * WBLK_BYTES, WBLK_BYTES, bar_w);
      for (int i = 0; i < NSLOT && i < ntiles; i++) issue_load(i);
      for (int k = NSLOT; k < NSLOT + 2; k++) prefetch(k);
    }
    __syncwarp();
    for (int i = 0; i < NSLOT && i < ntiles; i++) do_stats(i);

    for (int k = 0; k < ntiles; k++) {
      const int slot = k % NSLOT;
      const uint32_t sl = sbase + SM_SLOT + slot * SLOT_BYTES;
      const int tile = blockIdx.x + k * gridDim.x;
      mbar_wait(bar_out + 8 * slot, (k / NSLOT) & 1);
#pragma unroll
      for (int rg = 0; rg < 2; rg++) {
        const int row = 8 * pw + 4 * rg + (lane >> 3);
        __nv_bfloat16* orow;
        bool valid = true;
        if (STAGE == 1) {
          orow = out + ((size_t)(row & 3) * HW_DIM + (size_t)tile * 16 + (row >> 2)) * C_DIM;
        } else {
          const int t = tile >> 10, wh = (tile >> 5) & 31, ww = tile & 31;
          const int rh = row / 7;
          orow = out + ((size_t)t * HW_DIM + (size_t)(wh * 7 + rh) * 224 + ww * 7 + (row - rh * 7)) * C_DIM;
          valid = row < 49;
        }
        const uint32_t rb = sl + row * 128 + ((((lane & 7) ^ (row & 7))) << 4);
        uint4 v0 = lds_u4(rb), v1 = lds_u4(rb + BLK_BYTES), v2 = lds_u4(rb + 2 * BLK_BYTES);
        if (valid) {
          *reinterpret_cast<uint4*>(orow + (lane & 7) * 8) = v0;
          *reinterpret_cast<uint4*>(orow + 64 + (lane & 7) * 8) = v1;
          *reinterpret_cast<uint4*>(orow + 128 + (lane & 7) * 8) = v2;
        }
      }
      __syncwarp();
      if (lane == 0) mbar_arrive(bar_free + 8 * slot);
      if (k + NSLOT < ntiles) {
        if (pw == 0 && lane == 0) {
          mbar_wait(bar_free + 8 * slot, (k / NSLOT) & 1);
          issue_load(k + NSLOT);
          prefetch(k + NSLOT + 2);
        }
        __syncwarp();
        do_stats(k + NSLOT);
      }
    }
  } else {
    asm volatile("setmaxnreg.inc.sync.aligned.u32 208;");
    const int wg = warp >> 2;
    const int w = warp & 3;
    const int q = lane & 3, r = lane >> 2;
    const int row0 = 16 * w + r, row1 = row0 + 8;

    mbar_wait(bar_w, 0);
    if (tid < 192) {
      float s = 0.f;
      const uint32_t rowb = sbase + SM_WM + tid * 128;
#pragma unroll
      for (int kb = 0; kb < 3; kb++)
#pragma unroll
        for (int c = 0; c < 8; c++) {
          uint4 v = lds_u4(rowb + kb * WBLK_BYTES + ((c ^ (tid & 7)) << 4));
          s += (bf_lo(v.x) + bf_hi(v.x)) + (bf_lo(v.y) + bf_hi(v.y)) + (bf_lo(v.z) + bf_hi(v.z)) + (bf_lo(v.w) + bf_hi(v.w));
        }
      sts_f32(sbase + SM_MSUM + tid * 4, s);
    }
    named_bar_sync(3, 256);

    const uint64_t dW_M = make_desc(sbase + SM_WM, 16, 1024);
    const uint64_t dW_U = make_desc(sbase + SM_WU, 16, 1024);
    const uint64_t dOnes = make_desc(sbase + SM_ONES, 16, 1024);

    float acc[96];
    uint32_t pk[48];
    auto issue_A = [&](int i) {
      const uint64_t dXa = make_desc(sbase + SM_SLOT + (i % NSLOT) * SLOT_BYTES, 16, 1024);
      wg_fence();
#pragma unroll
      for (int kb = 0; kb < 3; kb++)
#pragma unroll
        for (int kk = 0; kk < 4; kk++)
          wgmma_m64n192k16_ss(acc, dXa + ((kb * BLK_BYTES + kk * 32) >> 4), dW_M + ((kb * WBLK_BYTES + kk * 32) >> 4),
                              (kb | kk) != 0);
      wg_commit();
    };
    if (wg < ntiles) mbar_wait(bar_full + 8 * wg, 0);
    issue_A(wg);

    for (int i = wg; i < ntiles; i += 2) {
      const int slot = i % NSLOT;
      const uint32_t par = (i / NSLOT) & 1;
      const uint32_t sl = sbase + SM_SLOT + slot * SLOT_BYTES;
      const uint32_t st = sbase + SM_STATS + slot * 1024;
      const uint64_t dX = make_desc(sl, 16, 1024);

      TL(0);
      mbar_wait(bar_ready + 8 * slot, par);
      TL(3);
      const float4 st0 = lds_f4(st + row0 * 16), st1 = lds_f4(st + row1 * 16);
      float2 msv[24];
#pragma unroll
      for (int j = 0; j < 24; j++) msv[j] = lds_f2(sbase + SM_MSUM + (8 * j + 2 * q) * 4);
      wg_wait0();
      fence_regs(acc);
      TL(4);
      constexpr int NJ = (STAGE == 1) ? 8 : 7;
      float sacc[4 * NJ];
      float gacc[4];
      {
        const float nm0 = -st0.y, nm1 = -st1.y;
        constexpr int NG = 1;
#pragma unroll
        for (int gb = 0; gb < NG; gb++) {
#pragma unroll
          for (int j = gb * (24 / NG); j < (gb + 1) * (24 / NG); j++) {
            const float2 ms = msv[j];
            pk[2 * j] = pack_bf16(fmaf(nm0, ms.x, acc[4 * j + 0]), fmaf(nm0, ms.y, acc[4 * j + 1]));
            pk[2 * j + 1] = pack_bf16(fmaf(nm1, ms.x, acc[4 * j + 2]), fmaf(nm1, ms.y, acc[4 * j + 3]));
          }
          wg_fence();
#pragma unroll
          for (int s = gb * (12 / NG); s < (gb + 1) * (12 / NG); s++) {
            const int kb = s >> 2, kk = s & 3;
            if constexpr (STAGE == 1) {
              wgmma_m64n64k16_rs(sacc, pk[4 * s + 0], pk[4 * s + 1], pk[4 * s + 2], pk[4 * s + 3],
                                 dX + ((kb * BLK_BYTES + kk * 32) >> 4), s != 0);
              wgmma_m64n8k16_rs(gacc, pk[4 * s + 0], pk[4 * s + 1], pk[4 * s + 2], pk[4 * s + 3], dOnes, s != 0);
            } else {
              wgmma_m64n56k16_rs(sacc, pk[4 * s + 0], pk[4 * s + 1], pk[4 * s + 2], pk[4 * s + 3],
                                 dX + ((kb * BLK_BYTES + kk * 32) >> 4), s != 0);
            }
          }
        }
        wg_commit();
      }
      TL(5);
      uint32_t pf[16];
      float linv0, linv1, cc0, cc1;
      if constexpr (STAGE == 1) {
        const float4 k00 = lds_f4(st + (16 * w + 2 * q) * 16), k01 = lds_f4(st + (16 * w + 2 * q + 1) * 16);
        const float4 k10 = lds_f4(st + (16 * w + 8 + 2 * q) * 16), k11 = lds_f4(st + (16 * w + 8 + 2 * q + 1) * 16);
        wg_wait0();
        fence_regs(sacc);
        fence_regs(gacc);
        TL(6);
        float s00 = sacc[0], s01 = sacc[1], s10 = sacc[6], s11 = sacc[7];
#pragma unroll
        for (int ww = 1; ww < 4; ww++)
          if (w == ww) { s00 = sacc[8 * ww]; s01 = sacc[8 * ww + 1]; s10 = sacc[8 * ww + 6]; s11 = sacc[8 * ww + 7]; }
        const bool v = (q >> 1) == (r >> 2);
        float u00 = fmaf(-k00.y, gacc[0], s00) * k00.z, u01 = fmaf(-k01.y, gacc[0], s01) * k01.z;
        float u10 = fmaf(-k10.y, gacc[2], s10) * k10.z, u11 = fmaf(-k11.y, gacc[2], s11) * k11.z;
        u00 = v ? u00 : -INFINITY; u01 = v ? u01 : -INFINITY; u10 = v ? u10 : -INFINITY; u11 = v ? u11 : -INFINITY;
        float mx0 = fmaxf(u00, u01), mx1 = fmaxf(u10, u11);
        mx0 = fmaxf(mx0, __shfl_xor_sync(0xffffffffu, mx0, 1));
        mx1 = fmaxf(mx1, __shfl_xor_sync(0xffffffffu, mx1, 1));
        mx0 = fmaxf(mx0, __shfl_xor_sync(0xffffffffu, mx0, 2));
        mx1 = fmaxf(mx1, __shfl_xor_sync(0xffffffffu, mx1, 2));
        const float b0 = -st0.x * mx0, b1 = -st1.x * mx1;
        const float p00 = ex2(fmaf(u00, st0.x, b0)), p01 = ex2(fmaf(u01, st0.x, b0));
        const float p10 = ex2(fmaf(u10, st1.x, b1)), p11 = ex2(fmaf(u11, st1.x, b1));
        float l0 = p00 + p01, l1 = p10 + p11;
        cc0 = fmaf(p00, k00.w, p01 * k01.w);
        cc1 = fmaf(p10, k10.w, p11 * k11.w);
        const uint32_t f0 = pack_bf16(p00 * k00.x, p01 * k01.x), f1 = pack_bf16(p10 * k10.x, p11 * k11.x);
#pragma unroll
        for (int s = 0; s < 4; s++) {
          pf[4 * s] = (w == s) ? f0 : 0u;
          pf[4 * s + 1] = 0u;
          pf[4 * s + 2] = 0u;
          pf[4 * s + 3] = (w == s) ? f1 : 0u;
        }
        l0 += __shfl_xor_sync(0xffffffffu, l0, 1);
        l1 += __shfl_xor_sync(0xffffffffu, l1, 1);
        cc0 += __shfl_xor_sync(0xffffffffu, cc0, 1);
        cc1 += __shfl_xor_sync(0xffffffffu, cc1, 1);
        l0 += __shfl_xor_sync(0xffffffffu, l0, 2);
        l1 += __shfl_xor_sync(0xffffffffu, l1, 2);
        cc0 += __shfl_xor_sync(0xffffffffu, cc0, 2);
        cc1 += __shfl_xor_sync(0xffffffffu, cc1, 2);
        linv0 = 1.0f / l0;
        linv1 = 1.0f / l1;
      } else {
        float4 kp[2 * NJ];
#pragma unroll
        for (int jj = 0; jj < NJ; jj++) {
          kp[2 * jj] = lds_f4(st + (8 * jj + 2 * q) * 16);
          kp[2 * jj + 1] = lds_f4(st + (8 * jj + 2 * q + 1) * 16);
        }
        wg_wait0();
        fence_regs(sacc);
        TL(6);
        const float gs0 = __shfl_sync(0xffffffffu, sacc[25], lane & ~3), gs1 = __shfl_sync(0xffffffffu, sacc[27], lane & ~3);
        float uv[4 * NJ];
        float mx0 = -INFINITY, mx1 = -INFINITY;
#pragma unroll
        for (int jj = 0; jj < NJ; jj++) {
          const int j0 = 8 * jj + 2 * q;
          const float4 k0 = kp[2 * jj], k1 = kp[2 * jj + 1];
          float u00 = fmaf(-k0.y, gs0, sacc[4 * jj + 0]) * k0.z;
          float u01 = fmaf(-k1.y, gs0, sacc[4 * jj + 1]) * k1.z;
          float u10 = fmaf(-k0.y, gs1, sacc[4 * jj + 2]) * k0.z;
          float u11 = fmaf(-k1.y, gs1, sacc[4 * jj + 3]) * k1.z;
          if (jj == 6) {
            const bool v0 = j0 < 49;
            u00 = v0 ? u00 : -INFINITY;
            u10 = v0 ? u10 : -INFINITY;
            u01 = -INFINITY;
            u11 = -INFINITY;
          }
          uv[4 * jj + 0] = u00; uv[4 * jj + 1] = u01; uv[4 * jj + 2] = u10; uv[4 * jj + 3] = u11;
          mx0 = fmaxf(mx0, fmaxf(u00, u01));
          mx1 = fmaxf(mx1, fmaxf(u10, u11));
        }
        mx0 = fmaxf(mx0, __shfl_xor_sync(0xffffffffu, mx0, 1));
        mx1 = fmaxf(mx1, __shfl_xor_sync(0xffffffffu, mx1, 1));
        mx0 = fmaxf(mx0, __shfl_xor_sync(0xffffffffu, mx0, 2));
        mx1 = fmaxf(mx1, __shfl_xor_sync(0xffffffffu, mx1, 2));
        const float b0 = -st0.x * mx0, b1 = -st1.x * mx1;
        float l0 = 0.f, l1 = 0.f;
        cc0 = 0.f; cc1 = 0.f;
#pragma unroll
        for (int jj = 0; jj < NJ; jj++) {
          const float4 k0 = kp[2 * jj], k1 = kp[2 * jj + 1];
          const float p00 = ex2(fmaf(uv[4 * jj + 0], st0.x, b0)), p01 = ex2(fmaf(uv[4 * jj + 1], st0.x, b0));
          const float p10 = ex2(fmaf(uv[4 * jj + 2], st1.x, b1)), p11 = ex2(fmaf(uv[4 * jj + 3], st1.x, b1));
          l0 += p00 + p01;
          l1 += p10 + p11;
          cc0 = fmaf(p00, k0.w, fmaf(p01, k1.w, cc0));
          cc1 = fmaf(p10, k0.w, fmaf(p11, k1.w, cc1));
          pf[2 * jj] = pack_bf16(p00 * k0.x, p01 * k1.x);
          pf[2 * jj + 1] = pack_bf16(p10 * k0.x, p11 * k1.x);
        }
        pf[14] = 0u;
        pf[15] = 0u;
        l0 += __shfl_xor_sync(0xffffffffu, l0, 1);
        l1 += __shfl_xor_sync(0xffffffffu, l1, 1);
        cc0 += __shfl_xor_sync(0xffffffffu, cc0, 1);
        cc1 += __shfl_xor_sync(0xffffffffu, cc1, 1);
        l0 += __shfl_xor_sync(0xffffffffu, l0, 2);
        l1 += __shfl_xor_sync(0xffffffffu, l1, 2);
        cc0 += __shfl_xor_sync(0xffffffffu, cc0, 2);
        cc1 += __shfl_xor_sync(0xffffffffu, cc1, 2);
        linv0 = (row0 < 49) ? 1.0f / l0 : 0.f;
        linv1 = (row1 < 49) ? 1.0f / l1 : 0.f;
      }
      TL(7);
      {
        const uint64_t dXt = make_desc(sl, BLK_BYTES, 1024);
        wg_fence();
#pragma unroll
        for (int s = 0; s < 4; s++)
          wgmma_m64n192k16_rs_tb(acc, pf[4 * s + 0], pf[4 * s + 1], pf[4 * s + 2], pf[4 * s + 3], dXt + ((s * 2048) >> 4),
                                 s != 0);
        wg_commit();
        wg_wait0();
        fence_regs(acc);
      }
      TL(8);
      {
        const float nc0 = -cc0 * linv0, nc1 = -cc1 * linv1;
#pragma unroll
        for (int j = 0; j < 24; j++) {
          pk[2 * j] = pack_bf16(fmaf(acc[4 * j + 0], linv0, nc0), fmaf(acc[4 * j + 1], linv0, nc0));
          pk[2 * j + 1] = pack_bf16(fmaf(acc[4 * j + 2], linv1, nc1), fmaf(acc[4 * j + 3], linv1, nc1));
        }
      }
      TL(9);
      wg_fence();
#pragma unroll
      for (int kb = 0; kb < 3; kb++)
#pragma unroll
        for (int kk = 0; kk < 4; kk++) {
          const int s = kb * 4 + kk;
          wgmma_m64n192k16_rs(acc, pk[4 * s + 0], pk[4 * s + 1], pk[4 * s + 2], pk[4 * s + 3],
                              dW_U + ((kb * WBLK_BYTES + kk * 32) >> 4), s != 0);
        }
      wg_commit();
      wg_wait0();
      fence_regs(acc);
      TL(10);
#pragma unroll
      for (int j = 0; j < 24; j++) {
        pk[2 * j] = pack_bf16(acc[4 * j + 0], acc[4 * j + 1]);
        pk[2 * j + 1] = pack_bf16(acc[4 * j + 2], acc[4 * j + 3]);
      }
      TL(1);
      {
        const int mrow = 16 * w + ((lane >> 3) & 1) * 8 + (lane & 7);
        const uint32_t abase = sl + mrow * 128;
#pragma unroll
        for (int j = 0; j < 24; j += 2) {
          const int chunk = j + (lane >> 4);
          const uint32_t addr = abase + (chunk >> 3) * BLK_BYTES + (((chunk & 7) ^ (lane & 7)) << 4);
          uint32_t x0, x1, x2, x3;
          ldsm_x4(addr, x0, x1, x2, x3);
          stsm_x4(addr, hadd2_bf16(x0, pk[2 * j]), hadd2_bf16(x1, pk[2 * j + 1]), hadd2_bf16(x2, pk[2 * j + 2]),
                  hadd2_bf16(x3, pk[2 * j + 3]));
        }
        __syncwarp();
        if (lane == 0) mbar_arrive(bar_out + 8 * slot);
      }
      if (i + 2 < ntiles) mbar_wait(bar_full + 8 * ((i + 2) % NSLOT), ((i + 2) / NSLOT) & 1);
      issue_A(i + 2);
      TL(11);
    }
    wg_wait0();
  }
}

typedef CUresult (*PFN_encodeTiled)(CUtensorMap*, CUtensorMapDataType, cuuint32_t, void*, const cuuint64_t*, const cuuint64_t*,
                                    const cuuint32_t*, const cuuint32_t*, CUtensorMapInterleave, CUtensorMapSwizzle,
                                    CUtensorMapL2promotion, CUtensorMapFloatOOBfill);

static PFN_encodeTiled get_encode() {
  static PFN_encodeTiled fn = nullptr;
  if (!fn) {
    void* p = nullptr;
    cudaDriverEntryPointQueryResult qres;
    cudaGetDriverEntryPoint("cuTensorMapEncodeTiled", &p, cudaEnableDefault, &qres);
    fn = (PFN_encodeTiled)p;
  }
  return fn;
}

extern "C" void kernel_launch(void* const* d_in, const int* in_sizes, int n_in, void* d_out, int out_size) {
  (void)in_sizes; (void)n_in; (void)out_size;
  const __nv_bfloat16* x = (const __nv_bfloat16*)d_in[0];
  const __nv_bfloat16* wqkv_t = (const __nv_bfloat16*)d_in[1];
  const __nv_bfloat16* wo_t = (const __nv_bfloat16*)d_in[2];
  const __nv_bfloat16* wqkv_s = (const __nv_bfloat16*)d_in[3];
  const __nv_bfloat16* wo_s = (const __nv_bfloat16*)d_in[4];
  PFN_encodeTiled enc = get_encode();

  CUtensorMap m1_in, m1_out, m2;
  {
    cuuint64_t dims[3] = {192, 4, 50176};
    cuuint64_t strides[2] = {(cuuint64_t)HW_DIM * 384, 384};
    cuuint32_t box[3] = {64, 4, 16};
    cuuint32_t es[3] = {1, 1, 1};
    enc(&m1_in, CU_TENSOR_MAP_DATA_TYPE_BFLOAT16, 3, (void*)x, dims, strides, box, es, CU_TENSOR_MAP_INTERLEAVE_NONE,
        CU_TENSOR_MAP_SWIZZLE_128B, CU_TENSOR_MAP_L2_PROMOTION_L2_256B, CU_TENSOR_MAP_FLOAT_OOB_FILL_NONE);
    enc(&m1_out, CU_TENSOR_MAP_DATA_TYPE_BFLOAT16, 3, d_out, dims, strides, box, es, CU_TENSOR_MAP_INTERLEAVE_NONE,
        CU_TENSOR_MAP_SWIZZLE_128B, CU_TENSOR_MAP_L2_PROMOTION_L2_256B, CU_TENSOR_MAP_FLOAT_OOB_FILL_NONE);
  }
  {
    cuuint64_t dims[4] = {192, 224, 224, 4};
    cuuint64_t strides[3] = {384, 224 * 384, (cuuint64_t)HW_DIM * 384};
    cuuint32_t box[4] = {64, 7, 7, 1};
    cuuint32_t es[4] = {1, 1, 1, 1};
    enc(&m2, CU_TENSOR_MAP_DATA_TYPE_BFLOAT16, 4, d_out, dims, strides, box, es, CU_TENSOR_MAP_INTERLEAVE_NONE,
        CU_TENSOR_MAP_SWIZZLE_128B, CU_TENSOR_MAP_L2_PROMOTION_L2_256B, CU_TENSOR_MAP_FLOAT_OOB_FILL_NONE);
  }
  const int smem = SM_TOTAL + 1024;
  cudaFuncSetAttribute(stage_kernel<1>, cudaFuncAttributeMaxDynamicSharedMemorySize, smem);
  cudaFuncSetAttribute(stage_kernel<2>, cudaFuncAttributeMaxDynamicSharedMemorySize, smem);
  int nsm = 132;
  cudaDeviceGetAttribute(&nsm, cudaDevAttrMultiProcessorCount, 0);

  merge_weights_kernel<<<288, 128>>>(wqkv_t, wo_t, wqkv_s, wo_s);
  cudaLaunchAttribute attr[1];
  attr[0].id = cudaLaunchAttributeProgrammaticStreamSerialization;
  attr[0].val.programmaticStreamSerializationAllowed = 1;
  cudaLaunchConfig_t cfg = {};
  cfg.gridDim = dim3(nsm);
  cfg.blockDim = dim3(512);
  cfg.dynamicSmemBytes = smem;
  cfg.stream = 0;
  cfg.attrs = attr;
  cfg.numAttrs = 1;
  cudaLaunchKernelEx(&cfg, stage_kernel<1>, m1_in, (__nv_bfloat16*)d_out);
  cudaLaunchKernelEx(&cfg, stage_kernel<2>, m2, (__nv_bfloat16*)d_out);
}
```

```cpp
#include <cuda_runtime.h>
#include <cuda_bf16.h>
#include <cuda.h>
#include <stdint.h>

#define C_DIM 192
#define T_DIM 4
#define HW_DIM 50176
#define NT1 3136
#define NT2 4096

#define SLOT_BYTES 24576
#define BLK_BYTES 8192
#define WMAT_BYTES 73728
#define WBLK_BYTES 24576
#define NSLOT 3

#define SM_WM 0
#define SM_WU WMAT_BYTES
#define SM_SLOT (2 * WMAT_BYTES)
#define SM_ONES (SM_SLOT + NSLOT * SLOT_BYTES)
#define SM_STATS (SM_ONES + 1024)
#define SM_MSUM (SM_STATS + NSLOT * 1024)
#define SM_BAR (SM_MSUM + 768)
#define SM_TOTAL (SM_BAR + 256)

__device__ __align__(1024) unsigned char g_wimg[2][2][WMAT_BYTES];
#define TL(idx)
#define TLP(idx)

__device__ __forceinline__ uint32_t smem_u32(const void* p) { return (uint32_t)__cvta_generic_to_shared(p); }

__device__ __forceinline__ void mbar_init(uint32_t bar, uint32_t count) {
  asm volatile("mbarrier.init.shared::cta.b64 [%0], %1;" ::"r"(bar), "r"(count) : "memory");
}
__device__ __forceinline__ void mbar_expect_tx(uint32_t bar, uint32_t bytes) {
  asm volatile("mbarrier.arrive.expect_tx.shared::cta.b64 _, [%0], %1;" ::"r"(bar), "r"(bytes) : "memory");
}
__device__ __forceinline__ void mbar_arrive(uint32_t bar) {
  asm volatile("mbarrier.arrive.shared::cta.b64 _, [%0];" ::"r"(bar) : "memory");
}
__device__ __forceinline__ bool mbar_try_wait(uint32_t bar, uint32_t parity) {
  uint32_t ok;
  asm volatile(
      "{\n.reg .pred p;\nmbarrier.try_wait.parity.shared::cta.b64 p, [%1], %2;\nselp.u32 %0, 1, 0, p;\n}\n"
      : "=r"(ok)
      : "r"(bar), "r"(parity)
      : "memory");
  return ok != 0;
}
__device__ __forceinline__ void mbar_wait(uint32_t bar, uint32_t parity) {
  for (uint32_t it = 0; it < (1u << 24); ++it)
    if (mbar_try_wait(bar, parity)) break;
}
__device__ __forceinline__ void fence_proxy_async() { asm volatile("fence.proxy.async.shared::cta;" ::: "memory"); }
__device__ __forceinline__ void named_bar_sync(int id, int nthreads) {
  asm volatile("bar.sync %0, %1;" ::"r"(id), "r"(nthreads) : "memory");
}

__device__ __forceinline__ void tma_load_3d(uint32_t dst, const CUtensorMap* map, int c0, int c1, int c2, uint32_t bar) {
  asm volatile(
      "cp.async.bulk.tensor.3d.shared::cluster.global.mbarrier::complete_tx::bytes [%0], [%1, {%3, %4, %5}], [%2];"
      ::"r"(dst), "l"(map), "r"(bar), "r"(c0), "r"(c1), "r"(c2) : "memory");
}
__device__ __forceinline__ void tma_load_4d(uint32_t dst, const CUtensorMap* map, int c0, int c1, int c2, int c3, uint32_t bar) {
  asm volatile(
      "cp.async.bulk.tensor.4d.shared::cluster.global.mbarrier::complete_tx::bytes [%0], [%1, {%3, %4, %5, %6}], [%2];"
      ::"r"(dst), "l"(map), "r"(bar), "r"(c0), "r"(c1), "r"(c2), "r"(c3) : "memory");
}
__device__ __forceinline__ void tma_store_3d(const CUtensorMap* map, uint32_t src, int c0, int c1, int c2) {
  asm volatile("cp.async.bulk.tensor.3d.global.shared::cta.bulk_group [%0, {%2, %3, %4}], [%1];"
               ::"l"(map), "r"(src), "r"(c0), "r"(c1), "r"(c2) : "memory");
}
__device__ __forceinline__ void tma_store_4d(const CUtensorMap* map, uint32_t src, int c0, int c1, int c2, int c3) {
  asm volatile("cp.async.bulk.tensor.4d.global.shared::cta.bulk_group [%0, {%2, %3, %4, %5}], [%1];"
               ::"l"(map), "r"(src), "r"(c0), "r"(c1), "r"(c2), "r"(c3) : "memory");
}
__device__ __forceinline__ void tma_red_add_3d(const CUtensorMap* map, uint32_t src, int c0, int c1, int c2) {
  asm volatile("cp.reduce.async.bulk.tensor.3d.global.shared::cta.add.tile.bulk_group [%0, {%2, %3, %4}], [%1];"
               ::"l"(map), "r"(src), "r"(c0), "r"(c1), "r"(c2) : "memory");
}
__device__ __forceinline__ void tma_red_add_4d(const CUtensorMap* map, uint32_t src, int c0, int c1, int c2, int c3) {
  asm volatile("cp.reduce.async.bulk.tensor.4d.global.shared::cta.add.tile.bulk_group [%0, {%2, %3, %4, %5}], [%1];"
               ::"l"(map), "r"(src), "r"(c0), "r"(c1), "r"(c2), "r"(c3) : "memory");
}
__device__ __forceinline__ void tma_prefetch_3d(const CUtensorMap* map, int c0, int c1, int c2) {
  asm volatile("cp.async.bulk.prefetch.tensor.3d.L2.global.tile [%0, {%1, %2, %3}];" ::"l"(map), "r"(c0), "r"(c1), "r"(c2) : "memory");
}
__device__ __forceinline__ void tma_prefetch_4d(const CUtensorMap* map, int c0, int c1, int c2, int c3) {
  asm volatile("cp.async.bulk.prefetch.tensor.4d.L2.global.tile [%0, {%1, %2, %3, %4}];" ::"l"(map), "r"(c0), "r"(c1), "r"(c2), "r"(c3) : "memory");
}
__device__ __forceinline__ void bulk_commit() { asm volatile("cp.async.bulk.commit_group;" ::: "memory"); }
__device__ __forceinline__ void bulk_wait_read0() { asm volatile("cp.async.bulk.wait_group.read 0;" ::: "memory"); }
__device__ __forceinline__ void bulk_wait0() { asm volatile("cp.async.bulk.wait_group 0;" ::: "memory"); }
__device__ __forceinline__ void bulk_load(uint32_t dst, const void* src, uint32_t bytes, uint32_t bar) {
  asm volatile("cp.async.bulk.shared::cluster.global.mbarrier::complete_tx::bytes [%0], [%1], %2, [%3];"
               ::"r"(dst), "l"(src), "r"(bytes), "r"(bar) : "memory");
}

__device__ __forceinline__ void wg_fence() { asm volatile("wgmma.fence.sync.aligned;" ::: "memory"); }
__device__ __forceinline__ void wg_commit() { asm volatile("wgmma.commit_group.sync.aligned;" ::: "memory"); }
__device__ __forceinline__ void wg_wait0() { asm volatile("wgmma.wait_group.sync.aligned 0;" ::: "memory"); }
template <int N>
__device__ __forceinline__ void fence_regs(float (&d)[N]) {
#pragma unroll
  for (int i = 0; i < N; i++) asm volatile("" : "+f"(d[i])::"memory");
}

__device__ __forceinline__ uint64_t make_desc(uint32_t addr, uint32_t lbo, uint32_t sbo) {
  return (uint64_t)((addr & 0x3FFFF) >> 4) | ((uint64_t)(lbo >> 4) << 16) | ((uint64_t)(sbo >> 4) << 32) | (1ull << 62);
}

__device__ __forceinline__ uint32_t pack_bf16(float lo, float hi) {
  uint32_t r;
  asm("cvt.rn.bf16x2.f32 %0, %1, %2;" : "=r"(r) : "f"(hi), "f"(lo));
  return r;
}
__device__ __forceinline__ uint32_t hadd2_bf16(uint32_t a, uint32_t b) {
  uint32_t r;
  asm("add.rn.bf16x2 %0, %1, %2;" : "=r"(r) : "r"(a), "r"(b));
  return r;
}
__device__ __forceinline__ bool __syncthreads_and_wg(bool pred, int id) {
  uint32_t res;
  asm volatile("{\n.reg .pred p, q;\nsetp.ne.u32 p, %1, 0;\nbar.red.and.pred q, %2, 128, p;\nselp.u32 %0, 1, 0, q;\n}\n"
               : "=r"(res) : "r"((uint32_t)pred), "r"(id) : "memory");
  return res != 0;
}
__device__ __forceinline__ float bf_lo(uint32_t v) { return __uint_as_float(v << 16); }
__device__ __forceinline__ float bf_hi(uint32_t v) { return __uint_as_float(v & 0xffff0000u); }

__device__ __forceinline__ void ldsm_x4(uint32_t addr, uint32_t& r0, uint32_t& r1, uint32_t& r2, uint32_t& r3) {
  asm volatile("ldmatrix.sync.aligned.m8n8.x4.shared.b16 {%0, %1, %2, %3}, [%4];"
               : "=r"(r0), "=r"(r1), "=r"(r2), "=r"(r3) : "r"(addr) : "memory");
}
__device__ __forceinline__ void stsm_x4(uint32_t addr, uint32_t r0, uint32_t r1, uint32_t r2, uint32_t r3) {
  asm volatile("stmatrix.sync.aligned.m8n8.x4.shared.b16 [%0], {%1, %2, %3, %4};"
               ::"r"(addr), "r"(r0), "r"(r1), "r"(r2), "r"(r3) : "memory");
}
__device__ __forceinline__ float4 lds_f4(uint32_t addr) {
  float4 v;
  asm volatile("ld.shared.v4.f32 {%0, %1, %2, %3}, [%4];" : "=f"(v.x), "=f"(v.y), "=f"(v.z), "=f"(v.w) : "r"(addr));
  return v;
}
__device__ __forceinline__ float2 lds_f2(uint32_t addr) {
  float2 v;
  asm volatile("ld.shared.v2.f32 {%0, %1}, [%2];" : "=f"(v.x), "=f"(v.y) : "r"(addr));
  return v;
}
__device__ __forceinline__ uint4 lds_u4(uint32_t addr) {
  uint4 v;
  asm volatile("ld.shared.v4.u32 {%0, %1, %2, %3}, [%4];" : "=r"(v.x), "=r"(v.y), "=r"(v.z), "=r"(v.w) : "r"(addr));
  return v;
}
__device__ __forceinline__ void sts_f4(uint32_t addr, float4 v) {
  asm volatile("st.shared.v4.f32 [%0], {%1, %2, %3, %4};" ::"r"(addr), "f"(v.x), "f"(v.y), "f"(v.z), "f"(v.w) : "memory");
}
__device__ __forceinline__ void sts_u4(uint32_t addr, uint4 v) {
  asm volatile("st.shared.v4.u32 [%0], {%1, %2, %3, %4};" ::"r"(addr), "r"(v.x), "r"(v.y), "r"(v.z), "r"(v.w) : "memory");
}
__device__ __forceinline__ void sts_f32(uint32_t addr, float v) {
  asm volatile("st.shared.f32 [%0], %1;" ::"r"(addr), "f"(v) : "memory");
}
__device__ __forceinline__ float ex2(float x) {
  float y;
  asm("ex2.approx.ftz.f32 %0, %1;" : "=f"(y) : "f"(x));
  return y;
}

__device__ __forceinline__ void wgmma_m64n192k16_ss(float (&d)[96], uint64_t descA, uint64_t descB, int scaleD) {
  asm volatile("{\n.reg .pred p;\nsetp.ne.b32 p, %98, 0;\n"
    "wgmma.mma_async.sync.aligned.m64n192k16.f32.bf16.bf16 "
    "{%0, %1, %2, %3, %4, %5, %6, %7, %8, %9, %10, %11, %12, %13, %14, %15, %16, %17, %18, %19, %20, %21, %22, %23, %24, %25, %26, %27, %28, %29, %30, %31, %32, %33, %34, %35, %36, %37, %38, %39, %40, %41, %42, %43, %44, %45, %46, %47, %48, %49, %50, %51, %52, %53, %54, %55, %56, %57, %58, %59, %60, %61, %62, %63, %64, %65, %66, %67, %68, %69, %70, %71, %72, %73, %74, %75, %76, %77, %78, %79, %80, %81, %82, %83, %84, %85, %86, %87, %88, %89, %90, %91, %92, %93, %94, %95}, %96, %97, p, 1, 1, 0, 0;\n}\n"
    : "+f"(d[0]), "+f"(d[1]), "+f"(d[2]), "+f"(d[3]), "+f"(d[4]), "+f"(d[5]), "+f"(d[6]), "+f"(d[7]), "+f"(d[8]), "+f"(d[9]), "+f"(d[10]), "+f"(d[11]), "+f"(d[12]), "+f"(d[13]), "+f"(d[14]), "+f"(d[15]), "+f"(d[16]), "+f"(d[17]), "+f"(d[18]), "+f"(d[19]), "+f"(d[20]), "+f"(d[21]), "+f"(d[22]), "+f"(d[23]), "+f"(d[24]), "+f"(d[25]), "+f"(d[26]), "+f"(d[27]), "+f"(d[28]), "+f"(d[29]), "+f"(d[30]), "+f"(d[31]), "+f"(d[32]), "+f"(d[33]), "+f"(d[34]), "+f"(d[35]), "+f"(d[36]), "+f"(d[37]), "+f"(d[38]), "+f"(d[39]), "+f"(d[40]), "+f"(d[41]), "+f"(d[42]), "+f"(d[43]), "+f"(d[44]), "+f"(d[45]), "+f"(d[46]), "+f"(d[47]), "+f"(d[48]), "+f"(d[49]), "+f"(d[50]), "+f"(d[51]), "+f"(d[52]), "+f"(d[53]), "+f"(d[54]), "+f"(d[55]), "+f"(d[56]), "+f"(d[57]), "+f"(d[58]), "+f"(d[59]), "+f"(d[60]), "+f"(d[61]), "+f"(d[62]), "+f"(d[63]), "+f"(d[64]), "+f"(d[65]), "+f"(d[66]), "+f"(d[67]), "+f"(d[68]), "+f"(d[69]), "+f"(d[70]), "+f"(d[71]), "+f"(d[72]), "+f"(d[73]), "+f"(d[74]), "+f"(d[75]), "+f"(d[76]), "+f"(d[77]), "+f"(d[78]), "+f"(d[79]), "+f"(d[80]), "+f"(d[81]), "+f"(d[82]), "+f"(d[83]), "+f"(d[84]), "+f"(d[85]), "+f"(d[86]), "+f"(d[87]), "+f"(d[88]), "+f"(d[89]), "+f"(d[90]), "+f"(d[91]), "+f"(d[92]), "+f"(d[93]), "+f"(d[94]), "+f"(d[95])
    : "l"(descA), "l"(descB), "r"(scaleD));
}

__device__ __forceinline__ void wgmma_m64n192k16_rs(float (&d)[96], uint32_t a0, uint32_t a1, uint32_t a2, uint32_t a3, uint64_t descB, int scaleD) {
  asm volatile("{\n.reg .pred p;\nsetp.ne.b32 p, %101, 0;\n"
    "wgmma.mma_async.sync.aligned.m64n192k16.f32.bf16.bf16 "
    "{%0, %1, %2, %3, %4, %5, %6, %7, %8, %9, %10, %11, %12, %13, %14, %15, %16, %17, %18, %19, %20, %21, %22, %23, %24, %25, %26, %27, %28, %29, %30, %31, %32, %33, %34, %35, %36, %37, %38, %39, %40, %41, %42, %43, %44, %45, %46, %47, %48, %49, %50, %51, %52, %53, %54, %55, %56, %57, %58, %59, %60, %61, %62, %63, %64, %65, %66, %67, %68, %69, %70, %71, %72, %73, %74, %75, %76, %77, %78, %79, %80, %81, %82, %83, %84, %85, %86, %87, %88, %89, %90, %91, %92, %93, %94, %95}, {%96, %97, %98, %99}, %100, p, 1, 1, 0;\n}\n"
    : "+f"(d[0]), "+f"(d[1]), "+f"(d[2]), "+f"(d[3]), "+f"(d[4]), "+f"(d[5]), "+f"(d[6]), "+f"(d[7]), "+f"(d[8]), "+f"(d[9]), "+f"(d[10]), "+f"(d[11]), "+f"(d[12]), "+f"(d[13]), "+f"(d[14]), "+f"(d[15]), "+f"(d[16]), "+f"(d[17]), "+f"(d[18]), "+f"(d[19]), "+f"(d[20]), "+f"(d[21]), "+f"(d[22]), "+f"(d[23]), "+f"(d[24]), "+f"(d[25]), "+f"(d[26]), "+f"(d[27]), "+f"(d[28]), "+f"(d[29]), "+f"(d[30]), "+f"(d[31]), "+f"(d[32]), "+f"(d[33]), "+f"(d[34]), "+f"(d[35]), "+f"(d[36]), "+f"(d[37]), "+f"(d[38]), "+f"(d[39]), "+f"(d[40]), "+f"(d[41]), "+f"(d[42]), "+f"(d[43]), "+f"(d[44]), "+f"(d[45]), "+f"(d[46]), "+f"(d[47]), "+f"(d[48]), "+f"(d[49]), "+f"(d[50]), "+f"(d[51]), "+f"(d[52]), "+f"(d[53]), "+f"(d[54]), "+f"(d[55]), "+f"(d[56]), "+f"(d[57]), "+f"(d[58]), "+f"(d[59]), "+f"(d[60]), "+f"(d[61]), "+f"(d[62]), "+f"(d[63]), "+f"(d[64]), "+f"(d[65]), "+f"(d[66]), "+f"(d[67]), "+f"(d[68]), "+f"(d[69]), "+f"(d[70]), "+f"(d[71]), "+f"(d[72]), "+f"(d[73]), "+f"(d[74]), "+f"(d[75]), "+f"(d[76]), "+f"(d[77]), "+f"(d[78]), "+f"(d[79]), "+f"(d[80]), "+f"(d[81]), "+f"(d[82]), "+f"(d[83]), "+f"(d[84]), "+f"(d[85]), "+f"(d[86]), "+f"(d[87]), "+f"(d[88]), "+f"(d[89]), "+f"(d[90]), "+f"(d[91]), "+f"(d[92]), "+f"(d[93]), "+f"(d[94]), "+f"(d[95])
    : "r"(a0), "r"(a1), "r"(a2), "r"(a3), "l"(descB), "r"(scaleD));
}

__device__ __forceinline__ void wgmma_m64n192k16_rs_tb(float (&d)[96], uint32_t a0, uint32_t a1, uint32_t a2, uint32_t a3, uint64_t descB, int scaleD) {
  asm volatile("{\n.reg .pred p;\nsetp.ne.b32 p, %101, 0;\n"
    "wgmma.mma_async.sync.aligned.m64n192k16.f32.bf16.bf16 "
    "{%0, %1, %2, %3, %4, %5, %6, %7, %8, %9, %10, %11, %12, %13, %14, %15, %16, %17, %18, %19, %20, %21, %22, %23, %24, %25, %26, %27, %28, %29, %30, %31, %32, %33, %34, %35, %36, %37, %38, %39, %40, %41, %42, %43, %44, %45, %46, %47, %48, %49, %50, %51, %52, %53, %54, %55, %56, %57, %58, %59, %60, %61, %62, %63, %64, %65, %66, %67, %68, %69, %70, %71, %72, %73, %74, %75, %76, %77, %78, %79, %80, %81, %82, %83, %84, %85, %86, %87, %88, %89, %90, %91, %92, %93, %94, %95}, {%96, %97, %98, %99}, %100, p, 1, 1, 1;\n}\n"
    : "+f"(d[0]), "+f"(d[1]), "+f"(d[2]), "+f"(d[3]), "+f"(d[4]), "+f"(d[5]), "+f"(d[6]), "+f"(d[7]), "+f"(d[8]), "+f"(d[9]), "+f"(d[10]), "+f"(d[11]), "+f"(d[12]), "+f"(d[13]), "+f"(d[14]), "+f"(d[15]), "+f"(d[16]), "+f"(d[17]), "+f"(d[18]), "+f"(d[19]), "+f"(d[20]), "+f"(d[21]), "+f"(d[22]), "+f"(d[23]), "+f"(d[24]), "+f"(d[25]), "+f"(d[26]), "+f"(d[27]), "+f"(d[28]), "+f"(d[29]), "+f"(d[30]), "+f"(d[31]), "+f"(d[32]), "+f"(d[33]), "+f"(d[34]), "+f"(d[35]), "+f"(d[36]), "+f"(d[37]), "+f"(d[38]), "+f"(d[39]), "+f"(d[40]), "+f"(d[41]), "+f"(d[42]), "+f"(d[43]), "+f"(d[44]), "+f"(d[45]), "+f"(d[46]), "+f"(d[47]), "+f"(d[48]), "+f"(d[49]), "+f"(d[50]), "+f"(d[51]), "+f"(d[52]), "+f"(d[53]), "+f"(d[54]), "+f"(d[55]), "+f"(d[56]), "+f"(d[57]), "+f"(d[58]), "+f"(d[59]), "+f"(d[60]), "+f"(d[61]), "+f"(d[62]), "+f"(d[63]), "+f"(d[64]), "+f"(d[65]), "+f"(d[66]), "+f"(d[67]), "+f"(d[68]), "+f"(d[69]), "+f"(d[70]), "+f"(d[71]), "+f"(d[72]), "+f"(d[73]), "+f"(d[74]), "+f"(d[75]), "+f"(d[76]), "+f"(d[77]), "+f"(d[78]), "+f"(d[79]), "+f"(d[80]), "+f"(d[81]), "+f"(d[82]), "+f"(d[83]), "+f"(d[84]), "+f"(d[85]), "+f"(d[86]), "+f"(d[87]), "+f"(d[88]), "+f"(d[89]), "+f"(d[90]), "+f"(d[91]), "+f"(d[92]), "+f"(d[93]), "+f"(d[94]), "+f"(d[95])
    : "r"(a0), "r"(a1), "r"(a2), "r"(a3), "l"(descB), "r"(scaleD));
}

__device__ __forceinline__ void wgmma_m64n64k16_rs(float (&d)[32], uint32_t a0, uint32_t a1, uint32_t a2, uint32_t a3, uint64_t descB, int scaleD) {
  asm volatile("{\n.reg .pred p;\nsetp.ne.b32 p, %37, 0;\n"
    "wgmma.mma_async.sync.aligned.m64n64k16.f32.bf16.bf16 "
    "{%0, %1, %2, %3, %4, %5, %6, %7, %8, %9, %10, %11, %12, %13, %14, %15, %16, %17, %18, %19, %20, %21, %22, %23, %24, %25, %26, %27, %28, %29, %30, %31}, {%32, %33, %34, %35}, %36, p, 1, 1, 0;\n}\n"
    : "+f"(d[0]), "+f"(d[1]), "+f"(d[2]), "+f"(d[3]), "+f"(d[4]), "+f"(d[5]), "+f"(d[6]), "+f"(d[7]), "+f"(d[8]), "+f"(d[9]), "+f"(d[10]), "+f"(d[11]), "+f"(d[12]), "+f"(d[13]), "+f"(d[14]), "+f"(d[15]), "+f"(d[16]), "+f"(d[17]), "+f"(d[18]), "+f"(d[19]), "+f"(d[20]), "+f"(d[21]), "+f"(d[22]), "+f"(d[23]), "+f"(d[24]), "+f"(d[25]), "+f"(d[26]), "+f"(d[27]), "+f"(d[28]), "+f"(d[29]), "+f"(d[30]), "+f"(d[31])
    : "r"(a0), "r"(a1), "r"(a2), "r"(a3), "l"(descB), "r"(scaleD));
}

__device__ __forceinline__ void wgmma_m64n56k16_rs(float (&d)[28], uint32_t a0, uint32_t a1, uint32_t a2, uint32_t a3, uint64_t descB, int scaleD) {
  asm volatile("{\n.reg .pred p;\nsetp.ne.b32 p, %33, 0;\n"
    "wgmma.mma_async.sync.aligned.m64n56k16.f32.bf16.bf16 "
    "{%0, %1, %2, %3, %4, %5, %6, %7, %8, %9, %10, %11, %12, %13, %14, %15, %16, %17, %18, %19, %20, %21, %22, %23, %24, %25, %26, %27}, {%28, %29, %30, %31}, %32, p, 1, 1, 0;\n}\n"
    : "+f"(d[0]), "+f"(d[1]), "+f"(d[2]), "+f"(d[3]), "+f"(d[4]), "+f"(d[5]), "+f"(d[6]), "+f"(d[7]), "+f"(d[8]), "+f"(d[9]), "+f"(d[10]), "+f"(d[11]), "+f"(d[12]), "+f"(d[13]), "+f"(d[14]), "+f"(d[15]), "+f"(d[16]), "+f"(d[17]), "+f"(d[18]), "+f"(d[19]), "+f"(d[20]), "+f"(d[21]), "+f"(d[22]), "+f"(d[23]), "+f"(d[24]), "+f"(d[25]), "+f"(d[26]), "+f"(d[27])
    : "r"(a0), "r"(a1), "r"(a2), "r"(a3), "l"(descB), "r"(scaleD));
}

__device__ __forceinline__ void wgmma_m64n8k16_rs(float (&d)[4], uint32_t a0, uint32_t a1, uint32_t a2, uint32_t a3, uint64_t descB, int scaleD) {
  asm volatile("{\n.reg .pred p;\nsetp.ne.b32 p, %9, 0;\n"
    "wgmma.mma_async.sync.aligned.m64n8k16.f32.bf16.bf16 "
    "{%0, %1, %2, %3}, {%4, %5, %6, %7}, %8, p, 1, 1, 0;\n}\n"
    : "+f"(d[0]), "+f"(d[1]), "+f"(d[2]), "+f"(d[3])
    : "r"(a0), "r"(a1), "r"(a2), "r"(a3), "l"(descB), "r"(scaleD));
}

__device__ float g_wbar[2][576];

__global__ void __launch_bounds__(768) wbar_kernel(const __nv_bfloat16* __restrict__ wqkv_t,
                                                   const __nv_bfloat16* __restrict__ wqkv_s) {
  asm volatile("griddepcontrol.launch_dependents;" ::: "memory");
  __shared__ float red[4][192];
  const int stage = blockIdx.x / 3, part = blockIdx.x % 3;
  const int c = threadIdx.x % 192, kg = threadIdx.x / 192;
  const __nv_bfloat16* w = (stage ? wqkv_s : wqkv_t) + (size_t)(kg * 48) * 576 + part * 192 + c;
  float acc = 0.f;
#pragma unroll 16
  for (int k = 0; k < 48; k++) acc += __bfloat162float(w[k * 576]);
  red[kg][c] = acc;
  __syncthreads();
  if (kg == 0) g_wbar[stage][part * 192 + c] = ((red[0][c] + red[1][c]) + (red[2][c] + red[3][c])) * (1.0f / 192.0f);
}

__global__ void __launch_bounds__(128) merge_weights_kernel(const __nv_bfloat16* __restrict__ wqkv_t,
                                                            const __nv_bfloat16* __restrict__ wo_t,
                                                            const __nv_bfloat16* __restrict__ wqkv_s,
                                                            const __nv_bfloat16* __restrict__ wo_s) {
  asm volatile("griddepcontrol.launch_dependents;" ::: "memory");
  const int gw = blockIdx.x * 4 + (threadIdx.x >> 5);
  const int lane = threadIdx.x & 31, g = lane >> 2, q = lane & 3;
  const int mat = gw / 288;
  const int kt = (gw % 288) / 24, nt = gw % 24;
  const __nv_bfloat16* wqkv = (mat < 2) ? wqkv_t : wqkv_s;
  const __nv_bfloat16* wo = (mat < 2) ? wo_t : wo_s;
  const bool isU = mat & 1;
  uint32_t af[12][4], bf[12][2];
  const __nv_bfloat16* arow0 = wqkv + (kt * 16 + g) * 576 + (isU ? 384 : 0) + 2 * q;
  const __nv_bfloat16* arow1 = arow0 + 8 * 576;
#pragma unroll
  for (int s = 0; s < 12; s++) {
    af[s][0] = *reinterpret_cast<const uint32_t*>(arow0 + 16 * s);
    af[s][1] = *reinterpret_cast<const uint32_t*>(arow1 + 16 * s);
    af[s][2] = *reinterpret_cast<const uint32_t*>(arow0 + 16 * s + 8);
    af[s][3] = *reinterpret_cast<const uint32_t*>(arow1 + 16 * s + 8);
  }
  if (!isU) {
    const __nv_bfloat16* brow = wqkv + (nt * 8 + g) * 576 + 192 + 2 * q;
#pragma unroll
    for (int s = 0; s < 12; s++) {
      bf[s][0] = *reinterpret_cast<const uint32_t*>(brow + 16 * s);
      bf[s][1] = *reinterpret_cast<const uint32_t*>(brow + 16 * s + 8);
    }
  } else {
    const unsigned short* bcol = reinterpret_cast<const unsigned short*>(wo) + (2 * q) * 192 + nt * 8 + g;
#pragma unroll
    for (int s = 0; s < 12; s++) {
      bf[s][0] = (uint32_t)bcol[(16 * s) * 192] | ((uint32_t)bcol[(16 * s + 1) * 192] << 16);
      bf[s][1] = (uint32_t)bcol[(16 * s + 8) * 192] | ((uint32_t)bcol[(16 * s + 9) * 192] << 16);
    }
  }
  float c[4] = {0.f, 0.f, 0.f, 0.f};
#pragma unroll
  for (int s = 0; s < 12; s++)
    asm volatile("mma.sync.aligned.m16n8k16.row.col.f32.bf16.bf16.f32 {%0,%1,%2,%3}, {%4,%5,%6,%7}, {%8,%9}, {%0,%1,%2,%3};"
                 : "+f"(c[0]), "+f"(c[1]), "+f"(c[2]), "+f"(c[3])
                 : "r"(af[s][0]), "r"(af[s][1]), "r"(af[s][2]), "r"(af[s][3]), "r"(bf[s][0]), "r"(bf[s][1]));
  asm volatile("griddepcontrol.wait;" ::: "memory");
  const float* abar = g_wbar[mat >> 1] + (isU ? 384 : 0) + 2 * q;
  const float* bbar = g_wbar[mat >> 1] + 192 + 2 * q;
  float r0 = 0.f, r1 = 0.f, ct = 0.f, gr = 0.f;
#pragma unroll
  for (int s = 0; s < 12; s++) {
#pragma unroll
    for (int h = 0; h < 2; h++) {
      const float2 ab = *reinterpret_cast<const float2*>(abar + 16 * s + 8 * h);
      ct = fmaf(bf_lo(bf[s][h]), ab.x, fmaf(bf_hi(bf[s][h]), ab.y, ct));
      if (!isU) {
        const float2 bb = *reinterpret_cast<const float2*>(bbar + 16 * s + 8 * h);
        r0 = fmaf(bf_lo(af[s][2 * h]), bb.x, fmaf(bf_hi(af[s][2 * h]), bb.y, r0));
        r1 = fmaf(bf_lo(af[s][2 * h + 1]), bb.x, fmaf(bf_hi(af[s][2 * h + 1]), bb.y, r1));
        gr = fmaf(ab.x, bb.x, fmaf(ab.y, bb.y, gr));
      }
    }
  }
#pragma unroll
  for (int o = 1; o < 4; o <<= 1) {
    r0 += __shfl_xor_sync(0xffffffffu, r0, o);
    r1 += __shfl_xor_sync(0xffffffffu, r1, o);
    ct += __shfl_xor_sync(0xffffffffu, ct, o);
    gr += __shfl_xor_sync(0xffffffffu, gr, o);
  }
  const float c0 = __shfl_sync(0xffffffffu, ct, 8 * q), c1 = __shfl_sync(0xffffffffu, ct, 8 * q + 4);
  c[0] += gr - r0 - c0;
  c[1] += gr - r0 - c1;
  c[2] += gr - r1 - c0;
  c[3] += gr - r1 - c1;
  unsigned char* img = g_wimg[mat >> 1][mat & 1];
#pragma unroll
  for (int j = 0; j < 4; j++) {
    const int k = kt * 16 + g + (j >> 1) * 8, nn = nt * 8 + 2 * q + (j & 1);
    size_t off = (size_t)(k / 64) * WBLK_BYTES + (size_t)nn * 128 + (size_t)((((k % 64) / 8) ^ (nn % 8)) * 16) + (k % 8) * 2;
    *reinterpret_cast<__nv_bfloat16*>(img + off) = __float2bfloat16(c[j]);
  }
}

template <int STAGE>
__global__ void __launch_bounds__(512, 1) stage_kernel(const __grid_constant__ CUtensorMap map_in,
                                                       __nv_bfloat16* __restrict__ out) {
  extern __shared__ unsigned char smem_raw[];
  const uint32_t sbase = (smem_u32(smem_raw) + 1023u) & ~1023u;
  const int tid = threadIdx.x;
  const int warp = tid >> 5, lane = tid & 31;
  const int NT = (STAGE == 1) ? NT1 : NT2;
  const uint32_t bar_full = sbase + SM_BAR;
  const uint32_t bar_ready = bar_full + 8 * NSLOT;
  const uint32_t bar_out = bar_ready + 8 * NSLOT;
  const uint32_t bar_free = bar_out + 8 * NSLOT;
  const uint32_t bar_w = bar_free + 8 * NSLOT;

  if (tid == 0) {
    for (int s = 0; s < NSLOT; s++) {
      mbar_init(bar_full + 8 * s, 1);
      mbar_init(bar_ready + 8 * s, 8);
      mbar_init(bar_out + 8 * s, 4);
      mbar_init(bar_free + 8 * s, 8);
    }
    mbar_init(bar_w, 1);
    asm volatile("fence.mbarrier_init.release.cluster;" ::: "memory");
  }
  if (STAGE == 2) {
    for (int i = tid; i < NSLOT * 3 * 15 * 8; i += 512) {
      int s = i / 360, r = i % 360;
      int blk = r / 120, rr = r % 120;
      uint32_t addr = sbase + SM_SLOT + s * SLOT_BYTES + blk * BLK_BYTES + (49 + rr / 8) * 128 + (rr % 8) * 16;
      sts_u4(addr, make_uint4(0, 0, 0, 0));
    }
  }
  fence_proxy_async();
  __syncthreads();

  const int ntiles = (NT - (int)blockIdx.x + (int)gridDim.x - 1) / (int)gridDim.x;

  if (warp >= 8) {
    asm volatile("setmaxnreg.dec.sync.aligned.u32 48;");
    const int pw = warp - 8;
    const int sq4 = lane & 3;

    auto issue_load = [&](int i) {
      const int slot = i % NSLOT;
      const uint32_t sl = sbase + SM_SLOT + slot * SLOT_BYTES;
      const int tile = blockIdx.x + i * gridDim.x;
      if (STAGE == 1) {
        mbar_expect_tx(bar_full + 8 * slot, 3 * BLK_BYTES);
        for (int cb = 0; cb < 3; cb++) tma_load_3d(sl + cb * BLK_BYTES, &map_in, cb * 64, 0, tile * 16, bar_full + 8 * slot);
      } else {
        const int t = tile >> 10, wh = (tile >> 5) & 31, ww = tile & 31;
        mbar_expect_tx(bar_full + 8 * slot, 3 * 49 * 128);
        for (int cb = 0; cb < 3; cb++) tma_load_4d(sl + cb * BLK_BYTES, &map_in, cb * 64, ww * 7, wh * 7, t, bar_full + 8 * slot);
      }
    };
    auto prefetch = [&](int k) {
      if (k < ntiles) {
        const int tp = blockIdx.x + k * gridDim.x;
        if (STAGE == 1) {
          for (int cb = 0; cb < 3; cb++) tma_prefetch_3d(&map_in, cb * 64, 0, tp * 16);
        } else {
          const int t = tp >> 10, wh = (tp >> 5) & 31, ww = tp & 31;
          for (int cb = 0; cb < 3; cb++) tma_prefetch_4d(&map_in, cb * 64, ww * 7, wh * 7, t);
        }
      }
    };
    auto do_stats = [&](int i) {
      const int slot = i % NSLOT;
      const uint32_t par = (i / NSLOT) & 1;
      const uint32_t sl = sbase + SM_SLOT + slot * SLOT_BYTES;
      mbar_wait(bar_full + 8 * slot, par);
      {
        const int srow = pw * 8 + (lane >> 2);
        const uint32_t rbase = sl + srow * 128;
        const uint32_t sx = (uint32_t)((srow & 7) << 4);
        float a0 = 0.f, a1 = 0.f, a2 = 0.f, a3 = 0.f, b0 = 0.f, b1 = 0.f, b2 = 0.f, b3 = 0.f;
        float pivot = 0.f;
#pragma unroll
        for (int hh = 0; hh < 2; hh++) {
          uint4 v[3];
#pragma unroll
          for (int c = 0; c < 3; c++) {
            const uint32_t chunk = sq4 * 6 + hh * 3 + c;
            v[c] = lds_u4(rbase + (chunk >> 3) * BLK_BYTES + (((chunk & 7) << 4) ^ sx));
          }
          if (hh == 0) pivot = bf_lo(__shfl_sync(0xffffffffu, v[0].x, lane & ~3));
#pragma unroll
          for (int c = 0; c < 3; c++) {
            float d0 = bf_lo(v[c].x) - pivot, d1 = bf_hi(v[c].x) - pivot, d2 = bf_lo(v[c].y) - pivot, d3 = bf_hi(v[c].y) - pivot;
            float d4 = bf_lo(v[c].z) - pivot, d5 = bf_hi(v[c].z) - pivot, d6 = bf_lo(v[c].w) - pivot, d7 = bf_hi(v[c].w) - pivot;
            a0 += d0 + d4; a1 += d1 + d5; a2 += d2 + d6; a3 += d3 + d7;
            b0 = fmaf(d0, d0, b0); b1 = fmaf(d1, d1, b1); b2 = fmaf(d2, d2, b2); b3 = fmaf(d3, d3, b3);
            b0 = fmaf(d4, d4, b0); b1 = fmaf(d5, d5, b1); b2 = fmaf(d6, d6, b2); b3 = fmaf(d7, d7, b3);
          }
        }
        float s1 = (a0 + a1) + (a2 + a3), s2 = (b0 + b1) + (b2 + b3);
        s1 += __shfl_xor_sync(0xffffffffu, s1, 1);
        s2 += __shfl_xor_sync(0xffffffffu, s2, 1);
        s1 += __shfl_xor_sync(0xffffffffu, s1, 2);
        s2 += __shfl_xor_sync(0xffffffffu, s2, 2);
        const float dm = s1 * (1.0f / 192.0f);
        const float var = fmaxf(fmaf(-dm, dm, s2 * (1.0f / 192.0f)), 0.f);
        const float rstd = rsqrtf(var + 1e-5f);
        if (sq4 == 0) {
          const float SC = 0.07216878364870322f * 1.4426950408889634f;
          asm volatile("st.shared.v2.f32 [%0], {%1, %2};" ::"r"(sbase + SM_STATS + slot * 1024 + srow * 8), "f"(rstd), "f"(rstd * SC) : "memory");
        }
      }
      __syncwarp();
      if (lane == 0) mbar_arrive(bar_ready + 8 * slot);
    };

    if (pw == 0 && lane == 0) {
      asm volatile("griddepcontrol.launch_dependents;" ::: "memory");
      asm volatile("griddepcontrol.wait;" ::: "memory");
      mbar_expect_tx(bar_w, 2 * WMAT_BYTES);
      const unsigned char* src = g_wimg[STAGE - 1][0];
      for (int i = 0; i < 6; i++) bulk_load(sbase + SM_WM + i * WBLK_BYTES, src + i * WBLK_BYTES, WBLK_BYTES, bar_w);
      for (int i = 0; i < NSLOT && i < ntiles; i++) issue_load(i);
      for (int k = NSLOT; k < NSLOT + 2; k++) prefetch(k);
    }
    __syncwarp();
    for (int i = 0; i < NSLOT && i < ntiles; i++) do_stats(i);

    for (int k = 0; k < ntiles; k++) {
      const int slot = k % NSLOT;
      const uint32_t sl = sbase + SM_SLOT + slot * SLOT_BYTES;
      const int tile = blockIdx.x + k * gridDim.x;
      if constexpr (STAGE == 2) {
        if (pw == 0 && lane == 0) {
          mbar_wait(bar_out + 8 * slot, (k / NSLOT) & 1);
          const int t = tile >> 10, wh = (tile >> 5) & 31, ww = tile & 31;
          for (int cb = 0; cb < 3; cb++) tma_red_add_4d(&map_in, sl + cb * BLK_BYTES, cb * 64, ww * 7, wh * 7, t);
          bulk_commit();
          if (k + NSLOT < ntiles) {
            bulk_wait_read0();
            issue_load(k + NSLOT);
            prefetch(k + NSLOT + 2);
          } else {
            bulk_wait0();
          }
        }
        __syncwarp();
        if (k + NSLOT < ntiles) do_stats(k + NSLOT);
        continue;
      }
      mbar_wait(bar_out + 8 * slot, (k / NSLOT) & 1);
#pragma unroll
      for (int rg = 0; rg < 2; rg++) {
        const int row = 8 * pw + 4 * rg + (lane >> 3);
        __nv_bfloat16* orow;
        bool valid = true;
        if (STAGE == 1) {
          orow = out + ((size_t)(row & 3) * HW_DIM + (size_t)tile * 16 + (row >> 2)) * C_DIM;
        } else {
          const int t = tile >> 10, wh = (tile >> 5) & 31, ww = tile & 31;
          const int rh = row / 7;
          orow = out + ((size_t)t * HW_DIM + (size_t)(wh * 7 + rh) * 224 + ww * 7 + (row - rh * 7)) * C_DIM;
          valid = row < 49;
        }
        const uint32_t rb = sl + row * 128 + ((((lane & 7) ^ (row & 7))) << 4);
        uint4 v0 = lds_u4(rb), v1 = lds_u4(rb + BLK_BYTES), v2 = lds_u4(rb + 2 * BLK_BYTES);
        if (valid) {
          *reinterpret_cast<uint4*>(orow + (lane & 7) * 8) = v0;
          *reinterpret_cast<uint4*>(orow + 64 + (lane & 7) * 8) = v1;
          *reinterpret_cast<uint4*>(orow + 128 + (lane & 7) * 8) = v2;
        }
      }
      __syncwarp();
      if (lane == 0) mbar_arrive(bar_free + 8 * slot);
      if (k + NSLOT < ntiles) {
        if (pw == 0 && lane == 0) {
          mbar_wait(bar_free + 8 * slot, (k / NSLOT) & 1);
          issue_load(k + NSLOT);
          prefetch(k + NSLOT + 2);
        }
        __syncwarp();
        do_stats(k + NSLOT);
      }
    }
  } else {
    asm volatile("setmaxnreg.inc.sync.aligned.u32 208;");
    const int wg = warp >> 2;
    const int w = warp & 3;
    const int q = lane & 3, r = lane >> 2;
    const int row0 = 16 * w + r, row1 = row0 + 8;

    mbar_wait(bar_w, 0);

    const uint64_t dW_M = make_desc(sbase + SM_WM, 16, 1024);
    const uint64_t dW_U = make_desc(sbase + SM_WU, 16, 1024);

    float acc[96];
    uint32_t pk[48];
    auto issue_A = [&](int i) {
      const uint64_t dXa = make_desc(sbase + SM_SLOT + (i % NSLOT) * SLOT_BYTES, 16, 1024);
      wg_fence();
#pragma unroll
      for (int kb = 0; kb < 3; kb++)
#pragma unroll
        for (int kk = 0; kk < 4; kk++)
          wgmma_m64n192k16_ss(acc, dXa + ((kb * BLK_BYTES + kk * 32) >> 4), dW_M + ((kb * WBLK_BYTES + kk * 32) >> 4),
                              (kb | kk) != 0);
      wg_commit();
    };
    if (wg < ntiles) mbar_wait(bar_full + 8 * wg, 0);
    issue_A(wg);

    for (int i = wg; i < ntiles; i += 2) {
      const int slot = i % NSLOT;
      const uint32_t par = (i / NSLOT) & 1;
      const uint32_t sl = sbase + SM_SLOT + slot * SLOT_BYTES;
      const uint32_t st = sbase + SM_STATS + slot * 1024;
      const uint64_t dX = make_desc(sl, 16, 1024);

      TL(0);
      mbar_wait(bar_ready + 8 * slot, par);
      TL(3);
      const float rs0 = lds_f2(st + row0 * 8).x, rs1 = lds_f2(st + row1 * 8).x;
      wg_wait0();
      fence_regs(acc);
      TL(4);
      constexpr int NJ = (STAGE == 1) ? 8 : 7;
      float sacc[4 * NJ];
      {
#pragma unroll
        for (int j = 0; j < 24; j++) {
          pk[2 * j] = pack_bf16(acc[4 * j + 0], acc[4 * j + 1]);
          pk[2 * j + 1] = pack_bf16(acc[4 * j + 2], acc[4 * j + 3]);
        }
        TL(2);
        wg_fence();
#pragma unroll
        for (int s = 0; s < 12; s++) {
          const int kb = s >> 2, kk = s & 3;
          if constexpr (STAGE == 1)
            wgmma_m64n64k16_rs(sacc, pk[4 * s + 0], pk[4 * s + 1], pk[4 * s + 2], pk[4 * s + 3],
                               dX + ((kb * BLK_BYTES + kk * 32) >> 4), s != 0);
          else
            wgmma_m64n56k16_rs(sacc, pk[4 * s + 0], pk[4 * s + 1], pk[4 * s + 2], pk[4 * s + 3],
                               dX + ((kb * BLK_BYTES + kk * 32) >> 4), s != 0);
        }
        wg_commit();
      }
      TL(5);
      uint32_t pf[16];
      if constexpr (STAGE == 1) {
        const float4 k0 = lds_f4(st + (16 * w + 2 * q) * 8), k1 = lds_f4(st + (16 * w + 8 + 2 * q) * 8);
        wg_wait0();
        fence_regs(sacc);
        TL(6);
        float s00 = sacc[0], s01 = sacc[1], s10 = sacc[6], s11 = sacc[7];
#pragma unroll
        for (int ww = 1; ww < 4; ww++)
          if (w == ww) { s00 = sacc[8 * ww]; s01 = sacc[8 * ww + 1]; s10 = sacc[8 * ww + 6]; s11 = sacc[8 * ww + 7]; }
        const bool v = (q >> 1) == (r >> 2);
        const float u00 = v ? s00 * k0.y : -INFINITY, u01 = v ? s01 * k0.w : -INFINITY;
        const float u10 = v ? s10 * k1.y : -INFINITY, u11 = v ? s11 * k1.w : -INFINITY;
        float mx0 = fmaxf(u00, u01), mx1 = fmaxf(u10, u11);
        mx0 = fmaxf(mx0, __shfl_xor_sync(0xffffffffu, mx0, 1));
        mx1 = fmaxf(mx1, __shfl_xor_sync(0xffffffffu, mx1, 1));
        mx0 = fmaxf(mx0, __shfl_xor_sync(0xffffffffu, mx0, 2));
        mx1 = fmaxf(mx1, __shfl_xor_sync(0xffffffffu, mx1, 2));
        const float b0 = -rs0 * mx0, b1 = -rs1 * mx1;
        const float p00 = ex2(fmaf(u00, rs0, b0)), p01 = ex2(fmaf(u01, rs0, b0));
        const float p10 = ex2(fmaf(u10, rs1, b1)), p11 = ex2(fmaf(u11, rs1, b1));
        float l0 = p00 + p01, l1 = p10 + p11;
        l0 += __shfl_xor_sync(0xffffffffu, l0, 1);
        l1 += __shfl_xor_sync(0xffffffffu, l1, 1);
        l0 += __shfl_xor_sync(0xffffffffu, l0, 2);
        l1 += __shfl_xor_sync(0xffffffffu, l1, 2);
        const float li0 = __frcp_rn(l0), li1 = __frcp_rn(l1);
        const uint32_t f0 = pack_bf16(p00 * (k0.x * li0), p01 * (k0.z * li0));
        const uint32_t f1 = pack_bf16(p10 * (k1.x * li1), p11 * (k1.z * li1));
#pragma unroll
        for (int s = 0; s < 4; s++) {
          pf[4 * s] = (w == s) ? f0 : 0u;
          pf[4 * s + 1] = 0u;
          pf[4 * s + 2] = 0u;
          pf[4 * s + 3] = (w == s) ? f1 : 0u;
        }
      } else {
        float4 kp[NJ];
#pragma unroll
        for (int jj = 0; jj < NJ; jj++) kp[jj] = lds_f4(st + (8 * jj + 2 * q) * 8);
        wg_wait0();
        fence_regs(sacc);
        TL(6);
        float uv[4 * NJ];
        float mx0 = -INFINITY, mx1 = -INFINITY;
#pragma unroll
        for (int jj = 0; jj < NJ; jj++) {
          float u00 = sacc[4 * jj + 0] * kp[jj].y, u01 = sacc[4 * jj + 1] * kp[jj].w;
          float u10 = sacc[4 * jj + 2] * kp[jj].y, u11 = sacc[4 * jj + 3] * kp[jj].w;
          if (jj == 6) {
            u00 = (q == 0) ? u00 : -INFINITY;
            u10 = (q == 0) ? u10 : -INFINITY;
            u01 = -INFINITY;
            u11 = -INFINITY;
          }
          uv[4 * jj + 0] = u00; uv[4 * jj + 1] = u01; uv[4 * jj + 2] = u10; uv[4 * jj + 3] = u11;
          mx0 = fmaxf(mx0, fmaxf(u00, u01));
          mx1 = fmaxf(mx1, fmaxf(u10, u11));
        }
        mx0 = fmaxf(mx0, __shfl_xor_sync(0xffffffffu, mx0, 1));
        mx1 = fmaxf(mx1, __shfl_xor_sync(0xffffffffu, mx1, 1));
        mx0 = fmaxf(mx0, __shfl_xor_sync(0xffffffffu, mx0, 2));
        mx1 = fmaxf(mx1, __shfl_xor_sync(0xffffffffu, mx1, 2));
        const float b0 = -rs0 * mx0, b1 = -rs1 * mx1;
        float l0 = 0.f, l1 = 0.f;
#pragma unroll
        for (int jj = 0; jj < NJ; jj++) {
          const float p00 = ex2(fmaf(uv[4 * jj + 0], rs0, b0)), p01 = ex2(fmaf(uv[4 * jj + 1], rs0, b0));
          const float p10 = ex2(fmaf(uv[4 * jj + 2], rs1, b1)), p11 = ex2(fmaf(uv[4 * jj + 3], rs1, b1));
          l0 += p00 + p01;
          l1 += p10 + p11;
          uv[4 * jj + 0] = p00 * kp[jj].x; uv[4 * jj + 1] = p01 * kp[jj].z;
          uv[4 * jj + 2] = p10 * kp[jj].x; uv[4 * jj + 3] = p11 * kp[jj].z;
        }
        l0 += __shfl_xor_sync(0xffffffffu, l0, 1);
        l1 += __shfl_xor_sync(0xffffffffu, l1, 1);
        l0 += __shfl_xor_sync(0xffffffffu, l0, 2);
        l1 += __shfl_xor_sync(0xffffffffu, l1, 2);
        const float li0 = (row0 < 49) ? __frcp_rn(l0) : 0.f, li1 = (row1 < 49) ? __frcp_rn(l1) : 0.f;
#pragma unroll
        for (int jj = 0; jj < NJ; jj++) {
          pf[2 * jj] = pack_bf16(uv[4 * jj + 0] * li0, uv[4 * jj + 1] * li0);
          pf[2 * jj + 1] = pack_bf16(uv[4 * jj + 2] * li1, uv[4 * jj + 3] * li1);
        }
        pf[14] = 0u;
        pf[15] = 0u;
      }
      TL(7);
      {
        const uint64_t dXt = make_desc(sl, BLK_BYTES, 1024);
        wg_fence();
#pragma unroll
        for (int s = 0; s < 4; s++)
          wgmma_m64n192k16_rs_tb(acc, pf[4 * s + 0], pf[4 * s + 1], pf[4 * s + 2], pf[4 * s + 3], dXt + ((s * 2048) >> 4),
                                 s != 0);
        wg_commit();
        wg_wait0();
        fence_regs(acc);
      }
      TL(8);
#pragma unroll
      for (int j = 0; j < 24; j++) {
        pk[2 * j] = pack_bf16(acc[4 * j + 0], acc[4 * j + 1]);
        pk[2 * j + 1] = pack_bf16(acc[4 * j + 2], acc[4 * j + 3]);
      }
      TL(9);
      wg_fence();
#pragma unroll
      for (int kb = 0; kb < 3; kb++)
#pragma unroll
        for (int kk = 0; kk < 4; kk++) {
          const int s = kb * 4 + kk;
          wgmma_m64n192k16_rs(acc, pk[4 * s + 0], pk[4 * s + 1], pk[4 * s + 2], pk[4 * s + 3],
                              dW_U + ((kb * WBLK_BYTES + kk * 32) >> 4), s != 0);
        }
      wg_commit();
      wg_wait0();
      fence_regs(acc);
      TL(10);
#pragma unroll
      for (int j = 0; j < 24; j++) {
        pk[2 * j] = pack_bf16(acc[4 * j + 0], acc[4 * j + 1]);
        pk[2 * j + 1] = pack_bf16(acc[4 * j + 2], acc[4 * j + 3]);
      }
      TL(1);
      {
        const int mrow = 16 * w + ((lane >> 3) & 1) * 8 + (lane & 7);
        const uint32_t abase = sl + mrow * 128;
#pragma unroll
        for (int j = 0; j < 24; j += 2) {
          const int chunk = j + (lane >> 4);
          const uint32_t addr = abase + (chunk >> 3) * BLK_BYTES + (((chunk & 7) ^ (lane & 7)) << 4);
          if constexpr (STAGE == 2) {
            stsm_x4(addr, pk[2 * j], pk[2 * j + 1], pk[2 * j + 2], pk[2 * j + 3]);
          } else {
            uint32_t x0, x1, x2, x3;
            ldsm_x4(addr, x0, x1, x2, x3);
            stsm_x4(addr, hadd2_bf16(x0, pk[2 * j]), hadd2_bf16(x1, pk[2 * j + 1]), hadd2_bf16(x2, pk[2 * j + 2]),
                    hadd2_bf16(x3, pk[2 * j + 3]));
          }
        }
        if constexpr (STAGE == 2) fence_proxy_async();
        __syncwarp();
        if (lane == 0) mbar_arrive(bar_out + 8 * slot);
      }
      TL(12);
      if (i + 2 < ntiles) mbar_wait(bar_full + 8 * ((i + 2) % NSLOT), ((i + 2) / NSLOT) & 1);
      TL(13);
      TL(14);
      issue_A(i + 2);
      TL(11);
    }
    wg_wait0();
  }
}

typedef CUresult (*PFN_encodeTiled)(CUtensorMap*, CUtensorMapDataType, cuuint32_t, void*, const cuuint64_t*, const cuuint64_t*,
                                    const cuuint32_t*, const cuuint32_t*, CUtensorMapInterleave, CUtensorMapSwizzle,
                                    CUtensorMapL2promotion, CUtensorMapFloatOOBfill);

static PFN_encodeTiled get_encode() {
  static PFN_encodeTiled fn = nullptr;
  if (!fn) {
    void* p = nullptr;
    cudaDriverEntryPointQueryResult qres;
    cudaGetDriverEntryPoint("cuTensorMapEncodeTiled", &p, cudaEnableDefault, &qres);
    fn = (PFN_encodeTiled)p;
  }
  return fn;
}

extern "C" void kernel_launch(void* const* d_in, const int* in_sizes, int n_in, void* d_out, int out_size) {
  (void)in_sizes; (void)n_in; (void)out_size;
  const __nv_bfloat16* x = (const __nv_bfloat16*)d_in[0];
  const __nv_bfloat16* wqkv_t = (const __nv_bfloat16*)d_in[1];
  const __nv_bfloat16* wo_t = (const __nv_bfloat16*)d_in[2];
  const __nv_bfloat16* wqkv_s = (const __nv_bfloat16*)d_in[3];
  const __nv_bfloat16* wo_s = (const __nv_bfloat16*)d_in[4];
  PFN_encodeTiled enc = get_encode();

  CUtensorMap m1_in, m1_out, m2;
  {
    cuuint64_t dims[3] = {192, 4, 50176};
    cuuint64_t strides[2] = {(cuuint64_t)HW_DIM * 384, 384};
    cuuint32_t box[3] = {64, 4, 16};
    cuuint32_t es[3] = {1, 1, 1};
    enc(&m1_in, CU_TENSOR_MAP_DATA_TYPE_BFLOAT16, 3, (void*)x, dims, strides, box, es, CU_TENSOR_MAP_INTERLEAVE_NONE,
        CU_TENSOR_MAP_SWIZZLE_128B, CU_TENSOR_MAP_L2_PROMOTION_L2_256B, CU_TENSOR_MAP_FLOAT_OOB_FILL_NONE);
    enc(&m1_out, CU_TENSOR_MAP_DATA_TYPE_BFLOAT16, 3, d_out, dims, strides, box, es, CU_TENSOR_MAP_INTERLEAVE_NONE,
        CU_TENSOR_MAP_SWIZZLE_128B, CU_TENSOR_MAP_L2_PROMOTION_L2_256B, CU_TENSOR_MAP_FLOAT_OOB_FILL_NONE);
  }
  {
    cuuint64_t dims[4] = {192, 224, 224, 4};
    cuuint64_t strides[3] = {384, 224 * 384, (cuuint64_t)HW_DIM * 384};
    cuuint32_t box[4] = {64, 7, 7, 1};
    cuuint32_t es[4] = {1, 1, 1, 1};
    enc(&m2, CU_TENSOR_MAP_DATA_TYPE_BFLOAT16, 4, d_out, dims, strides, box, es, CU_TENSOR_MAP_INTERLEAVE_NONE,
        CU_TENSOR_MAP_SWIZZLE_128B, CU_TENSOR_MAP_L2_PROMOTION_L2_256B, CU_TENSOR_MAP_FLOAT_OOB_FILL_NONE);
  }
  const int smem = SM_TOTAL + 1024;
  cudaFuncSetAttribute(stage_kernel<1>, cudaFuncAttributeMaxDynamicSharedMemorySize, smem);
  cudaFuncSetAttribute(stage_kernel<2>, cudaFuncAttributeMaxDynamicSharedMemorySize, smem);
  int nsm = 132;
  cudaDeviceGetAttribute(&nsm, cudaDevAttrMultiProcessorCount, 0);

  wbar_kernel<<<6, 768>>>(wqkv_t, wqkv_s);
  cudaLaunchAttribute attr[1];
  attr[0].id = cudaLaunchAttributeProgrammaticStreamSerialization;
  attr[0].val.programmaticStreamSerializationAllowed = 1;
  cudaLaunchConfig_t cfg = {};
  cfg.gridDim = dim3(nsm);
  cfg.blockDim = dim3(512);
  cfg.dynamicSmemBytes = smem;
  cfg.stream = 0;
  cfg.attrs = attr;
  cfg.numAttrs = 1;
  {
    cudaLaunchConfig_t cm = cfg;
    cm.gridDim = dim3(288);
    cm.blockDim = dim3(128);
    cm.dynamicSmemBytes = 0;
    cudaLaunchKernelEx(&cm, merge_weights_kernel, wqkv_t, wo_t, wqkv_s, wo_s);
  }
  cudaLaunchKernelEx(&cfg, stage_kernel<1>, m1_in, (__nv_bfloat16*)d_out);
  cudaLaunchKernelEx(&cfg, stage_kernel<2>, m2, (__nv_bfloat16*)d_out);
}
```
